```python
import torch

def _softmax(x, axis=-1):
    return torch.softmax(x, dim=axis)
def _gelu(x):
    return torch.nn.functional.gelu(x, approximate="tanh")
def _silu(x):
    return torch.nn.functional.silu(x)
def _sigmoid(x):
    return torch.sigmoid(x)
def _layernorm(x, axis=-1, eps=1e-5):
    m = x.mean(dim=axis, keepdim=True)
    v = x.var(dim=axis, keepdim=True, unbiased=False)
    return (x - m) / torch.sqrt(v + eps)
def _scatter_add(tgt, idx, src, axis=0):
    return tgt.clone().index_add_(axis, idx, src)
def _segment_sum(src, seg, n):
    out = torch.zeros((n,) + src.shape[1:], dtype=src.dtype)
    return out.index_add_(0, seg, src)
def _pad(x, pw):
    flat = tuple(v for pair in reversed(pw) for v in pair)
    return torch.nn.functional.pad(x, flat)

kernel_name = 'standalone__edge_featured_mpnn_mpnn__graph'

def setup_inputs():

    _w = (lambda a: (lambda t: t.to(torch.bfloat16) if t.is_floating_point() else t)(torch.as_tensor(a)))
    N, deg, D, De = 25000, 32, 64, max(16, 1)
    E = N * deg
    H = 2 * D
    return {
        "x": _w((lambda *s: torch.randn(*s, dtype=torch.bfloat16) * 0.05)(N, D)),
        "e_attr": _w((lambda *s: torch.randn(*s, dtype=torch.bfloat16) * 0.8)(E, De)),
        "src": _w((lambda lo, hi, *s: torch.randint(lo, hi, s))(0, N, E).to(torch.int64)),
        "dst": _w((lambda lo, hi, *s: torch.randint(lo, hi, s))(0, N, E).to(torch.int64)),
        "w1": _w((lambda *s: torch.randn(*s, dtype=torch.bfloat16) * 0.8)(2 * D + De, H) * (1.0 / (2 * D + De) ** 0.5)),
        "b1": _w((lambda *s: torch.randn(*s, dtype=torch.bfloat16) * 0.8)(H) * 0.01),
        "w2": _w((lambda *s: torch.randn(*s, dtype=torch.bfloat16) * 0.05)(H, D) * (1.0 / H ** 0.5)),
        "b2": _w((lambda *s: torch.randn(*s, dtype=torch.bfloat16) * 0.05)(D) * 0.01),
    }

def reference(x, e_attr, src, dst, w1, b1, w2, b2):
    N, D = x.shape
    h_src = x[src]
    h_dst = x[dst]
    m_in = torch.concatenate([h_src, h_dst, e_attr], axis=-1)
    h = _silu(m_in @ w1 + b1)
    msg = h @ w2 + b2
    return _segment_sum(msg, dst, N)
```

```cpp
#include <cuda_runtime.h>
#include <cuda_bf16.h>
#include <cuda_fp16.h>
#include <stdint.h>

namespace {

constexpr int N_NODES = 25000;
constexpr int N_EDGES = 800000;
constexpr int NCTA = 132;
constexpr int NPC = 190;
constexpr int CHUNK = 6064;

#define NSTREAM 2
constexpr int NS = NSTREAM;
constexpr int NCW = 2 * NS;
constexpr int NT = 128 * (NCW + 1);
constexpr int NW = NT / 32;
constexpr int G = 4 * NS;
constexpr int R = 10;
constexpr int PD = R - NS - 1;
constexpr int ROWS = 192 + 8 * G;
constexpr int SMAX = 111;
constexpr int OVFCAP = 256;
constexpr int NV = (CHUNK / 4 + NT - 1) / NT;
constexpr int NX = (192 * 8 + NT - 1) / NT;
constexpr int NR = (NCTA + NW - 1) / NW;

constexpr int OFF_XR = 0;
constexpr int OFF_ER = OFF_XR + R * 8192;
constexpr int OFF_MR = OFF_ER + R * 2048;
constexpr int OFF_QH = ((OFF_MR + R * 128 + 1023) / 1024) * 1024;
constexpr int OFF_EID = OFF_QH + 2 * ROWS * 128;
constexpr int OFF_SRC = OFF_EID + SMAX * 256;
constexpr int OFF_CNT = OFF_SRC + SMAX * 128;
constexpr int OFF_OFF = OFF_CNT + 136 * 4;
constexpr int OFF_SEG = OFF_OFF + 136 * 4;
constexpr int OFF_KEY = OFF_SEG + 136 * 4;
constexpr int OFF_EV = OFF_KEY + 192 * 4;
constexpr int OFF_SRK = OFF_EV + (SMAX + 5) * 4;
constexpr int OFF_NOD = OFF_SRK + 192;
constexpr int OFF_OVF = OFF_NOD + 192;
constexpr int OFF_BAR = OFF_OVF + OVFCAP * 8;
constexpr int OFF_MISC = OFF_BAR + 2 * R * 8;
constexpr int SMEM_USED = OFF_MISC + 64;
constexpr int SMEM_BYTES = SMEM_USED + 1024;
constexpr int OFF_STG = OFF_XR;
constexpr int OFF_XO = ((CHUNK * 8 + 1023) / 1024) * 1024;
constexpr int OFF_W1 = OFF_EID;
constexpr int OFF_W2 = OFF_EID;
constexpr int OFF_OUT = OFF_XR;
static_assert(OFF_XO + 192 * 128 <= OFF_QH, "alias");
static_assert(144 * 272 <= SMAX * 384, "alias");
static_assert(128 * 144 <= SMAX * 256, "alias");
static_assert(SMEM_BYTES <= 232448, "smem");
static_assert(OFF_OVF % 8 == 0 && OFF_BAR % 8 == 0 && OFF_KEY % 16 == 0 && OFF_EID % 16 == 0, "align");

__device__ uint2 g_ent[NCTA * CHUNK];
__device__ uint32_t g_tab[NCTA * NCTA];
__device__ uint4 g_x16[(N_NODES + 1) * 8];

__device__ __forceinline__ void wg_fence() { asm volatile("wgmma.fence.sync.aligned;" ::: "memory"); }
__device__ __forceinline__ void wg_commit() { asm volatile("wgmma.commit_group.sync.aligned;" ::: "memory"); }
__device__ __forceinline__ void wg_wait0() { asm volatile("wgmma.wait_group.sync.aligned 0;" ::: "memory"); }
template <int M> __device__ __forceinline__ void fence_regs(uint32_t (&d)[M]) {
#pragma unroll
    for (int i = 0; i < M; i++) asm volatile("" : "+r"(d[i])::"memory");
}
template <int M> __device__ __forceinline__ void fence_regs(float (&d)[M]) {
#pragma unroll
    for (int i = 0; i < M; i++) asm volatile("" : "+f"(d[i])::"memory");
}
constexpr uint32_t HI128 = 0x40000040;
constexpr uint32_t HI32 = 0xC0000010;
template <int SC, uint32_t HI>
__device__ __forceinline__ void mma64h(uint32_t (&d)[16], const uint32_t (&a)[4], uint32_t lo) {
    asm volatile("{\n.reg .pred p;\n.reg .b64 dsc;\nsetp.ne.b32 p, %21, 0;\nmov.b64 dsc, {%20, %22};\n"
        "wgmma.mma_async.sync.aligned.m64n64k16.f16.f16.f16 {%0, %1, %2, %3, %4, %5, %6, %7, %8, %9, %10, %11, %12, %13, %14, %15}, {%16, %17, %18, %19}, dsc, p, 1, 1, 0;\n}\n"
        : "+r"(d[0]), "+r"(d[1]), "+r"(d[2]), "+r"(d[3]), "+r"(d[4]), "+r"(d[5]), "+r"(d[6]), "+r"(d[7]),
          "+r"(d[8]), "+r"(d[9]), "+r"(d[10]), "+r"(d[11]), "+r"(d[12]), "+r"(d[13]), "+r"(d[14]), "+r"(d[15])
        : "r"(a[0]), "r"(a[1]), "r"(a[2]), "r"(a[3]), "r"(lo), "n"(SC), "n"(HI));
}
template <int SC>
__device__ __forceinline__ void mma32f(float (&d)[16], const uint32_t (&a)[4], uint32_t lo) {
    asm volatile("{\n.reg .pred p;\n.reg .b64 dsc;\nsetp.ne.b32 p, %21, 0;\nmov.b64 dsc, {%20, %22};\n"
        "wgmma.mma_async.sync.aligned.m64n32k16.f32.f16.f16 {%0, %1, %2, %3, %4, %5, %6, %7, %8, %9, %10, %11, %12, %13, %14, %15}, {%16, %17, %18, %19}, dsc, p, 1, 1, 0;\n}\n"
        : "+f"(d[0]), "+f"(d[1]), "+f"(d[2]), "+f"(d[3]), "+f"(d[4]), "+f"(d[5]), "+f"(d[6]), "+f"(d[7]),
          "+f"(d[8]), "+f"(d[9]), "+f"(d[10]), "+f"(d[11]), "+f"(d[12]), "+f"(d[13]), "+f"(d[14]), "+f"(d[15])
        : "r"(a[0]), "r"(a[1]), "r"(a[2]), "r"(a[3]), "r"(lo), "n"(SC), "n"(HI128));
}
__device__ __forceinline__ uint32_t hadd2(uint32_t a, uint32_t b) { uint32_t r; asm("add.rn.f16x2 %0, %1, %2;" : "=r"(r) : "r"(a), "r"(b)); return r; }
__device__ __forceinline__ uint32_t hfma2(uint32_t a, uint32_t b, uint32_t c) { uint32_t r; asm("fma.rn.f16x2 %0, %1, %2, %3;" : "=r"(r) : "r"(a), "r"(b), "r"(c)); return r; }
__device__ __forceinline__ uint32_t htanh2(uint32_t a) { uint32_t r; asm("tanh.approx.f16x2 %0, %1;" : "=r"(r) : "r"(a)); return r; }
__device__ __forceinline__ uint32_t pack_h2(float lo, float hi) { uint32_t r; asm("cvt.rn.f16x2.f32 %0, %1, %2;" : "=r"(r) : "f"(hi), "f"(lo)); return r; }
__device__ __forceinline__ uint32_t pack_b2(float lo, float hi) { uint32_t r; asm("cvt.rn.bf16x2.f32 %0, %1, %2;" : "=r"(r) : "f"(hi), "f"(lo)); return r; }
__device__ __forceinline__ uint32_t bf2h(uint32_t v) { return pack_h2(__uint_as_float(v << 16), __uint_as_float(v & 0xffff0000u)); }
__device__ __forceinline__ uint32_t bf2h_half(uint32_t v) { return pack_h2(0.5f * __uint_as_float(v << 16), 0.5f * __uint_as_float(v & 0xffff0000u)); }
__device__ __forceinline__ uint4 bf2h4(uint4 v) { return make_uint4(bf2h(v.x), bf2h(v.y), bf2h(v.z), bf2h(v.w)); }

__device__ __forceinline__ void cp16(uint32_t s, const void* g) { asm volatile("cp.async.cg.shared.global [%0], [%1], 16;" ::"r"(s), "l"(g) : "memory"); }
__device__ __forceinline__ void cp16z(uint32_t s, const void* g, uint32_t sz) { asm volatile("cp.async.cg.shared.global [%0], [%1], 16, %2;" ::"r"(s), "l"(g), "r"(sz) : "memory"); }
__device__ __forceinline__ void cp_commit() { asm volatile("cp.async.commit_group;" ::: "memory"); }
template <int N> __device__ __forceinline__ void cp_wait() { asm volatile("cp.async.wait_group %0;" ::"n"(N) : "memory"); }
__device__ __forceinline__ void proxy_fence() { asm volatile("fence.proxy.async.shared::cta;" ::: "memory"); }
__device__ __forceinline__ bool mbar_try(uint32_t bar, uint32_t parity) {
    uint32_t ok;
    asm volatile("{\n.reg .pred p;\nmbarrier.try_wait.parity.shared::cta.b64 p, [%1], %2;\nselp.u32 %0, 1, 0, p;\n}" : "=r"(ok) : "r"(bar), "r"(parity) : "memory");
    return ok;
}
__device__ __forceinline__ void mbar_wait(uint32_t bar, uint32_t parity) {
    for (int it = 0; it < (1 << 20); it++) if (mbar_try(bar, parity)) break;
}
__device__ __forceinline__ void mbar_arrive(uint32_t bar) { asm volatile("mbarrier.arrive.shared::cta.b64 _, [%0];" ::"r"(bar) : "memory"); }
__device__ __forceinline__ uint32_t lds32(uint32_t a) { uint32_t r; asm volatile("ld.shared.u32 %0, [%1];" : "=r"(r) : "r"(a) : "memory"); return r; }
__device__ __forceinline__ uint32_t lds8(uint32_t a) { uint32_t r; asm volatile("ld.shared.u8 %0, [%1];" : "=r"(r) : "r"(a) : "memory"); return r; }
__device__ __forceinline__ uint2 lds64(uint32_t a) { uint2 r; asm volatile("ld.shared.v2.u32 {%0,%1}, [%2];" : "=r"(r.x), "=r"(r.y) : "r"(a) : "memory"); return r; }
__device__ __forceinline__ uint4 lds128(uint32_t a) { uint4 r; asm volatile("ld.shared.v4.u32 {%0,%1,%2,%3}, [%4];" : "=r"(r.x), "=r"(r.y), "=r"(r.z), "=r"(r.w) : "r"(a) : "memory"); return r; }
__device__ __forceinline__ void sts128(uint32_t a, uint4 v) { asm volatile("st.shared.v4.u32 [%0], {%1,%2,%3,%4};" ::"r"(a), "r"(v.x), "r"(v.y), "r"(v.z), "r"(v.w) : "memory"); }
__device__ __forceinline__ void sts64(uint32_t a, uint32_t x, uint32_t y) { asm volatile("st.shared.v2.u32 [%0], {%1,%2};" ::"r"(a), "r"(x), "r"(y) : "memory"); }
__device__ __forceinline__ void sts32(uint32_t a, uint32_t v) { asm volatile("st.shared.u32 [%0], %1;" ::"r"(a), "r"(v) : "memory"); }
__device__ __forceinline__ void sts16(uint32_t a, uint32_t v) { asm volatile("st.shared.u16 [%0], %1;" ::"r"(a), "h"((uint16_t)v) : "memory"); }
__device__ __forceinline__ void sts8(uint32_t a, uint32_t v) { asm volatile("st.shared.u8 [%0], %1;" ::"r"(a), "r"(v) : "memory"); }
__device__ __forceinline__ uint32_t atoms_add(uint32_t a, uint32_t v) { uint32_t r; asm volatile("atom.shared.add.u32 %0, [%1], %2;" : "=r"(r) : "r"(a), "r"(v) : "memory"); return r; }
__device__ __forceinline__ void ldsm4t(uint32_t (&r)[4], uint32_t a) {
    asm volatile("ldmatrix.sync.aligned.m8n8.x4.trans.shared.b16 {%0,%1,%2,%3}, [%4];" : "=r"(r[0]), "=r"(r[1]), "=r"(r[2]), "=r"(r[3]) : "r"(a) : "memory");
}
__device__ __forceinline__ void ldsm2t(uint32_t& r0, uint32_t& r1, uint32_t a) {
    asm volatile("ldmatrix.sync.aligned.m8n8.x2.trans.shared.b16 {%0,%1}, [%2];" : "=r"(r0), "=r"(r1) : "r"(a) : "memory");
}
__device__ __forceinline__ void stsm2t(uint32_t a, uint32_t r0, uint32_t r1) {
    asm volatile("stmatrix.sync.aligned.m8n8.x2.trans.shared.b16 [%0], {%1,%2};" ::"r"(a), "r"(r0), "r"(r1) : "memory");
}
__device__ __forceinline__ void stsm4t(uint32_t a, uint32_t r0, uint32_t r1, uint32_t r2, uint32_t r3) {
    asm volatile("stmatrix.sync.aligned.m8n8.x4.trans.shared.b16 [%0], {%1,%2,%3,%4};" ::"r"(a), "r"(r0), "r"(r1), "r"(r2), "r"(r3) : "memory");
}
__device__ __forceinline__ void named_bar(int id, int n) { asm volatile("bar.sync %0, %1;" ::"r"(id), "r"(n) : "memory"); }
__device__ __forceinline__ float bf2f(const __nv_bfloat16* p) { return __bfloat162float(*p); }

struct LineMap {
    int L0, rem;
    __device__ __forceinline__ void map(int y, int& k, int& gg) const {
        int s = 0, y0 = 0;
#pragma unroll
        for (int i = 1; i < NS; i++) { int Y = 4 * (i * L0 + min(i, rem)); if (y >= Y) { s = i; y0 = Y; } }
        int Ls = L0 + (s < rem ? 1 : 0);
        int yy = y - y0;
        gg = (yy >= Ls) + (yy >= 2 * Ls) + (yy >= 3 * Ls);
        k = (yy - gg * Ls) * NS + s;
    }
};

__device__ __noinline__ void slow_path(uint8_t* sp, const __nv_bfloat16* x, const __nv_bfloat16* ea, const __nv_bfloat16* w1,
                                       const __nv_bfloat16* b1, const __nv_bfloat16* w2, const __nv_bfloat16* b2, __nv_bfloat16* out) {
    const int tid = threadIdx.x, lane = tid & 31, warp = tid >> 5, cta = blockIdx.x;
    const int nrows = min(NPC, N_NODES - cta * NPC);
    float* hs = (float*)sp;
    __nv_bfloat16* w1s = (__nv_bfloat16*)(sp + 192 * 128 * 4);
    int* dg = (int*)(sp + 192 * 128 * 4 + 144 * 128 * 2);
    const uint32_t* seg = (const uint32_t*)(sp + OFF_SEG);
    __syncthreads();
    for (int i = tid; i < 192 * 128; i += NT) hs[i] = 0.f;
    for (int i = tid; i < 144 * 128; i += NT) w1s[i] = w1[i];
    for (int i = tid; i < 192; i += NT) dg[i] = 0;
    __syncthreads();
    float bb[4];
    for (int j = 0; j < 4; j++) bb[j] = bf2f(b1 + lane * 4 + j);
    for (int p = 0; p < NCTA; p++) {
        uint32_t sg = seg[p];
        int st = (sg >> 13) & 0x1fff, cnt = sg & 0x1fff;
        for (int i = warp; i < cnt; i += NW) {
            uint2 en = __ldcg(&g_ent[p * CHUNK + st + i]);
            int eid = en.x & 0xfffff, dl = en.x >> 20, s = en.y;
            float v[5];
            v[0] = bf2f(x + s * 64 + lane); v[1] = bf2f(x + s * 64 + 32 + lane);
            v[2] = bf2f(x + (cta * NPC + dl) * 64 + lane); v[3] = bf2f(x + (cta * NPC + dl) * 64 + 32 + lane);
            v[4] = lane < 16 ? bf2f(ea + (size_t)eid * 16 + lane) : 0.f;
            float z[4] = {bb[0], bb[1], bb[2], bb[3]};
#pragma unroll
            for (int c = 0; c < 5; c++) {
                for (int kk = 0; kk < (c == 4 ? 16 : 32); kk++) {
                    float a = __shfl_sync(0xffffffffu, v[c], kk);
                    const __nv_bfloat16* wr = w1s + (c * 32 + kk) * 128 + lane * 4;
#pragma unroll
                    for (int j = 0; j < 4; j++) z[j] = fmaf(a, __bfloat162float(wr[j]), z[j]);
                }
            }
#pragma unroll
            for (int j = 0; j < 4; j++) atomicAdd(&hs[dl * 128 + lane * 4 + j], z[j] / (1.f + expf(-z[j])));
            if (lane == 0) atomicAdd(&dg[dl], 1);
        }
    }
    __syncthreads();
    for (int i = tid; i < nrows * 64; i += NT) {
        int n = i >> 6, d = i & 63;
        float a = 0.f;
        if (dg[n] > 0) {
            a = (float)dg[n] * bf2f(b2 + d);
            for (int h = 0; h < 128; h++) a = fmaf(hs[n * 128 + h], bf2f(w2 + h * 64 + d), a);
        }
        out[(size_t)(cta * NPC + n) * 64 + d] = __float2bfloat16(a);
    }
}

__global__ void __launch_bounds__(NT, 1)
mpnn_kernel(const __nv_bfloat16* __restrict__ x, const __nv_bfloat16* __restrict__ ea, const int* __restrict__ src,
            const int* __restrict__ dst, const __nv_bfloat16* __restrict__ w1, const __nv_bfloat16* __restrict__ b1,
            const __nv_bfloat16* __restrict__ w2, const __nv_bfloat16* __restrict__ b2, __nv_bfloat16* __restrict__ out, int mode) {
    extern __shared__ uint8_t smem_raw[];
    const uint32_t sraw = (uint32_t)__cvta_generic_to_shared(smem_raw);
    const uint32_t sb = (sraw + 1023) & ~1023u;
    uint8_t* sp = smem_raw + (sb - sraw);
    const int tid = threadIdx.x, lane = tid & 31;
    const int warp = __shfl_sync(0xffffffffu, tid >> 5, 0);
    const int wg = warp >> 2;
    const int cta = blockIdx.x;
    const int nrows = min(NPC, N_NODES - cta * NPC);
    const int e0 = cta * CHUNK;
    const int nvec = min(CHUNK, N_EDGES - e0) >> 2;

    int4 d4[NV], s4[NV];
    if (mode & 1) {
#pragma unroll
        for (int v = 0; v < NV; v++) {
            int i = tid + v * NT;
            if (i < nvec) { d4[v] = __ldg((const int4*)(dst + e0) + i); s4[v] = __ldg((const int4*)(src + e0) + i); }
        }
    }
    uint4 xr[NX];
#pragma unroll
    for (int v = 0; v < NX; v++) {
        int i = tid + v * NT;
        xr[v] = make_uint4(0, 0, 0, 0);
        if (i < nrows * 8) xr[v] = __ldg((const uint4*)x + cta * NPC * 8 + i);
    }
    for (int i = tid; i < 144 * 16; i += NT) cp16(sb + OFF_W1 + (i >> 4) * 272 + (i & 15) * 16, w1 + i * 8);
    cp_commit();
    if (tid < 136) sts32(sb + OFF_CNT + tid * 4, 0);
    if (tid < 192) sts32(sb + OFF_KEY + tid * 4, tid);
    if (tid < SMAX + 5) sts32(sb + OFF_EV + tid * 4, 0);
    if (tid < 16) sts32(sb + OFF_MISC + tid * 4, 0);
    if (tid < R) {
        asm volatile("mbarrier.init.shared::cta.b64 [%0], 4;" ::"r"(sb + OFF_BAR + tid * 8) : "memory");
        asm volatile("mbarrier.init.shared::cta.b64 [%0], 8;" ::"r"(sb + OFF_BAR + (R + tid) * 8) : "memory");
    }
    __syncthreads();

    uint32_t key[NV * 4];
    if (mode & 1) {
#pragma unroll
        for (int v = 0; v < NV; v++) {
            if (tid + v * NT < nvec) {
                int dd[4] = {d4[v].x, d4[v].y, d4[v].z, d4[v].w};
#pragma unroll
                for (int j = 0; j < 4; j++) {
                    uint32_t c = (uint32_t)dd[j] / (uint32_t)NPC;
                    uint32_t dl = dd[j] - c * NPC;
                    uint32_t rk = atoms_add(sb + OFF_CNT + c * 4, 1);
                    key[v * 4 + j] = c | (rk << 8) | (dl << 21);
                }
            }
        }
    }
#pragma unroll
    for (int v = 0; v < NX; v++) {
        int i = tid + v * NT;
        if (i < 192 * 8) {
            uint4 h = bf2h4(xr[v]);
            int row = i >> 3, ch = i & 7;
            sts128(sb + OFF_XO + row * 128 + ((ch ^ (row & 7)) << 4), h);
            if ((mode & 1) && i < nrows * 8) g_x16[cta * NPC * 8 + i] = h;
        }
    }
    proxy_fence();
    cp_wait<0>();
    __syncthreads();

    if (mode & 1) {
        if (warp == 0) {
            uint32_t c[5], sum = 0;
#pragma unroll
            for (int j = 0; j < 5; j++) { int i = lane * 5 + j; c[j] = i < NCTA ? lds32(sb + OFF_CNT + i * 4) : 0; sum += c[j]; }
            uint32_t inc = sum;
#pragma unroll
            for (int o = 1; o < 32; o <<= 1) { uint32_t t = __shfl_up_sync(0xffffffffu, inc, o); if (lane >= o) inc += t; }
            uint32_t ex = inc - sum;
#pragma unroll
            for (int j = 0; j < 5; j++) { int i = lane * 5 + j; if (i < NCTA) sts32(sb + OFF_OFF + i * 4, ex); ex += c[j]; }
        }
        __syncthreads();
#pragma unroll
        for (int v = 0; v < NV; v++) {
            int i = tid + v * NT;
            if (i < nvec) {
                int ss[4] = {s4[v].x, s4[v].y, s4[v].z, s4[v].w};
#pragma unroll
                for (int j = 0; j < 4; j++) {
                    uint32_t kk = key[v * 4 + j];
                    uint32_t pos = lds32(sb + OFF_OFF + (kk & 255) * 4) + ((kk >> 8) & 0x1fff);
                    sts64(sb + OFF_STG + pos * 8, (uint32_t)(e0 + i * 4 + j) | ((kk >> 21) << 20), (uint32_t)ss[j]);
                }
            }
        }
        __syncthreads();
        for (int i = tid; i < nvec * 2; i += NT) ((uint4*)(g_ent + e0))[i] = lds128(sb + OFF_STG + i * 16);
        __syncthreads();
    }

    uint32_t w[5][4];
    const int hh = wg & 1, strm = wg >> 1, wq = warp & 3;
    if (wg == NCW) {
        const int pt = tid - NCW * 128;
        if (mode & 1) {
            __threadfence();
            for (int c = pt; c < NCTA; c += 128) {
                uint32_t v = 0x80000000u | (lds32(sb + OFF_OFF + c * 4) << 13) | lds32(sb + OFF_CNT + c * 4);
                asm volatile("st.relaxed.gpu.global.u32 [%0], %1;" ::"l"(g_tab + c * NCTA + cta), "r"(v) : "memory");
            }
        }
        if (mode & 2) {
            for (int p = pt; p < NCTA; p += 128) {
                uint32_t v = 0;
                for (int it = 0; it < (1 << 22); it++) {
                    asm volatile("ld.relaxed.gpu.global.u32 %0, [%1];" : "=r"(v) : "l"(g_tab + cta * NCTA + p) : "memory");
                    if (v) break;
                }
                sts32(sb + OFF_SEG + p * 4, v);
                g_tab[cta * NCTA + p] = 0;
            }
            __threadfence();
        }
    } else if (mode & 2) {
        const int h0 = hh * 64 + wq * 16;
        const uint32_t wa = sb + OFF_W1 + (((lane >> 4) & 1) * 8 + (lane & 7)) * 272 + (h0 + ((lane >> 3) & 1) * 8) * 2;
        uint32_t wb[4][4];
#pragma unroll
        for (int i = 0; i < 4; i++) {
            ldsm4t(w[i], wa + i * 16 * 272);
            ldsm4t(wb[i], wa + (64 + i * 16) * 272);
        }
        ldsm4t(w[4], wa + 128 * 272);
#pragma unroll
        for (int i = 0; i < 5; i++)
#pragma unroll
            for (int j = 0; j < 4; j++) { w[i][j] = bf2h_half(w[i][j]); if (i < 4) wb[i][j] = bf2h_half(wb[i][j]); }
        float bl0 = 0.5f * bf2f(b1 + h0 + (lane >> 2)), bl1 = 0.5f * bf2f(b1 + h0 + 8 + (lane >> 2));
        uint32_t bq[2] = {pack_h2(bl0, bl0), pack_h2(bl1, bl1)};
        for (int nb = strm; nb < 3; nb += NS) {
            uint32_t acc[16];
#pragma unroll
            for (int i = 0; i < 16; i++) acc[i] = 0;
            uint32_t lo = ((sb + OFF_XO + nb * 8192) >> 4) | 0x10000;
#pragma unroll
            for (int i = 0; i < 4; i++) fence_regs(wb[i]);
            fence_regs(acc);
            wg_fence();
            mma64h<0, HI128>(acc, wb[0], lo);
            mma64h<1, HI128>(acc, wb[1], lo + 2);
            mma64h<1, HI128>(acc, wb[2], lo + 4);
            mma64h<1, HI128>(acc, wb[3], lo + 6);
            wg_commit();
            wg_wait0();
            fence_regs(acc);
#pragma unroll
            for (int j = 0; j < 8; j += 2) {
                int row = nb * 64 + (j + (lane >> 4)) * 8 + (lane & 7);
                uint32_t a = sb + OFF_QH + hh * ROWS * 128 + row * 128 + (((wq * 2 + ((lane >> 3) & 1)) ^ (row & 7)) << 4);
                stsm4t(a, hadd2(acc[2 * j], bq[0]), hadd2(acc[2 * j + 1], bq[1]), hadd2(acc[2 * j + 2], bq[0]), hadd2(acc[2 * j + 3], bq[1]));
            }
        }
    }
    if (!(mode & 2)) return;
    __syncthreads();

    uint32_t en0[NR * 2], en1[NR * 2];
    uint32_t vmask = 0;
#pragma unroll
    for (int r = 0; r < NR; r++) {
        int p = warp + r * NW;
        if (p < NCTA) {
            uint32_t sg = lds32(sb + OFF_SEG + p * 4);
            int st = (sg >> 13) & 0x1fff, cnt = sg & 0x1fff;
#pragma unroll
            for (int j = 0; j < 2; j++) {
                if (lane + 32 * j < cnt) {
                    uint2 t = __ldcg(&g_ent[p * CHUNK + st + lane + 32 * j]);
                    en0[r * 2 + j] = t.x; en1[r * 2 + j] = t.y;
                    vmask |= 1u << (r * 2 + j);
                }
            }
        }
    }
    for (int i = tid; i < SMAX * 16; i += NT) sts128(sb + OFF_EID + i * 16, make_uint4(0x80000000u, 0x80000000u, 0x80000000u, 0x80000000u));
    {
        const uint32_t z = N_NODES | (N_NODES << 16);
        for (int i = tid; i < SMAX * 8; i += NT) sts128(sb + OFF_SRC + i * 16, make_uint4(z, z, z, z));
    }
#pragma unroll
    for (int r = 0; r < NR; r++) {
        int p = warp + r * NW;
        if (p < NCTA) {
            uint32_t sg = lds32(sb + OFF_SEG + p * 4);
            int st = (sg >> 13) & 0x1fff, cnt = sg & 0x1fff;
            for (int i = 64 + lane; i < cnt; i += 32) {
                uint2 t = __ldcg(&g_ent[p * CHUNK + st + i]);
                uint32_t rk = atoms_add(sb + OFF_KEY + (t.x >> 20) * 4, 256) >> 8;
                uint32_t o = atoms_add(sb + OFF_MISC, 1);
                if (o < OVFCAP) sts64(sb + OFF_OVF + o * 8, t.x, t.y | (min(rk, 0xffffu) << 16));
            }
        }
    }
#pragma unroll
    for (int r = 0; r < NR * 2; r++) {
        if (vmask & (1u << r)) {
            uint32_t rk = atoms_add(sb + OFF_KEY + (en0[r] >> 20) * 4, 256) >> 8;
            en1[r] |= min(rk, 0xffffu) << 16;
        }
    }
    __syncthreads();

    constexpr int TPN = NT >= 768 ? 4 : 2;
    if (tid < 192 * TPN) {
        int n = tid / TPN, part = tid % TPN;
        uint32_t mk = lds32(sb + OFF_KEY + n * 4);
        int c = 0;
#pragma unroll
        for (int i = 0; i < 48 / TPN; i++) {
            uint4 t = lds128(sb + OFF_KEY + (part * (48 / TPN) + i) * 16);
            c += (t.x > mk) + (t.y > mk) + (t.z > mk) + (t.w > mk);
        }
        c += __shfl_xor_sync(0xffffffffu, c, 1);
        if (TPN == 4) c += __shfl_xor_sync(0xffffffffu, c, 2);
        if (part == 0) { sts8(sb + OFF_SRK + n, c); sts8(sb + OFF_NOD + c, n); }
    }
    __syncthreads();

    int len = 0;
    if (lane < 24) len = ((lds32(sb + OFF_KEY + lds8(sb + OFF_NOD + lane * 8) * 4) >> 8) + 1) >> 1;
    int inc = len;
#pragma unroll
    for (int o = 1; o < 32; o <<= 1) { int t = __shfl_up_sync(0xffffffffu, inc, o); if (lane >= o) inc += t; }
    const int pos = inc - len;
    const int tot = __shfl_sync(0xffffffffu, inc, 31);
    const int Stot = (tot + 3) >> 2;
    const int novf = lds32(sb + OFF_MISC);
    if (Stot > SMAX || novf > OVFCAP) { slow_path(sp, x, ea, w1, b1, w2, b2, out); return; }
    LineMap lm;
    lm.L0 = Stot / NS; lm.rem = Stot - lm.L0 * NS;
    if (warp == NW - 1) {
        if (len > 0) { int k, gg; lm.map(pos, k, gg); sts8(sb + OFF_EV + k * 4 + gg, 1 + lane); }
#pragma unroll
        for (int g = 1; g < G; g++) {
            int s = g >> 2, Ls = lm.L0 + (s < lm.rem ? 1 : 0);
            int Y = 4 * (s * lm.L0 + min(s, lm.rem)) + (g & 3) * Ls;
            uint32_t le = __ballot_sync(0xffffffffu, len > 0 && pos <= Y);
            uint32_t eq = __ballot_sync(0xffffffffu, len > 0 && pos == Y);
            if (lane == 0 && Y < tot && Ls > 0 && !eq) sts8(sb + OFF_EV + s * 4 + (g & 3), 32 + __popc(le));
        }
    }
    auto place = [&](uint32_t a, uint32_t b, bool valid) {
        uint32_t sr = valid ? lds8(sb + OFF_SRK + (a >> 20)) : 0;
        int p0 = __shfl_sync(0xffffffffu, pos, sr >> 3);
        if (valid) {
            int rk = b >> 16, k, gg;
            lm.map(p0 + (rk >> 1), k, gg);
            int row = (rk & 1) * 32 + gg * 8 + (sr & 7);
            sts32(sb + OFF_EID + k * 256 + row * 4, a & 0xfffff);
            sts16(sb + OFF_SRC + k * 128 + ((row & 15) * 4 + (row >> 4)) * 2, b & 0xffff);
        }
    };
#pragma unroll
    for (int r = 0; r < NR * 2; r++) place(en0[r], en1[r], (vmask >> r) & 1);
    for (int i0 = warp * 32; i0 < novf; i0 += NT) {
        int i = i0 + lane;
        uint2 t = make_uint2(0, 0);
        if (i < novf) t = lds64(sb + OFF_OVF + i * 8);
        place(t.x, t.y, i < novf);
    }
    __syncthreads();

    const uint32_t bar_full = sb + OFF_BAR, bar_empty = sb + OFF_BAR + R * 8;
    if (wg == NCW) {
        const int pt = tid - NCW * 128;
        const uint32_t xdst = sb + OFF_XR + (pt >> 3) * 128 + (((pt & 7) ^ ((pt >> 3) & 7)) << 4);
        const uint32_t edst = sb + OFF_ER + (pt >> 1) * 32 + (((pt & 1) ^ ((pt >> 3) & 1)) << 4);
        const int er = pt >> 1;
        const uint32_t mdst = sb + OFF_MR + (((er & 7) >> 1) * 8 + (er >> 3)) * 4 + (er & 1) * 2;
        const char* xg = (const char*)g_x16 + (pt & 7) * 16;
        const char* eg = (const char*)ea + (pt & 1) * 16;
        int st = 0, pe = 1, sj = 0;
        for (int k = 0; k < Stot + PD; k++) {
            if (k < Stot) {
                uint2 si = lds64(sb + OFF_SRC + k * 128 + (pt >> 3) * 8);
                uint32_t ei = lds32(sb + OFF_EID + k * 256 + er * 4);
                mbar_wait(bar_empty + st * 8, pe);
                cp16z(edst + st * 2048, eg + (size_t)(ei & 0xfffff) * 32, (ei >> 31) ? 0 : 16);
                cp16(xdst + st * 8192, xg + (si.x & 0xffff) * 128);
                cp16(xdst + st * 8192 + 2048, xg + (si.x >> 16) * 128);
                cp16(xdst + st * 8192 + 4096, xg + (si.y & 0xffff) * 128);
                cp16(xdst + st * 8192 + 6144, xg + (si.y >> 16) * 128);
                if (!(pt & 1)) sts16(mdst + st * 128, (ei >> 31) ? 0 : 0x3c00);
                if (++st == R) { st = 0; pe ^= 1; }
            }
            cp_commit();
            if (k >= PD) {
                cp_wait<PD>();
                sts128(edst + sj * 2048, bf2h4(lds128(edst + sj * 2048)));
                proxy_fence();
                __syncwarp();
                if (lane == 0) mbar_arrive(bar_full + sj * 8);
                if (++sj == R) sj = 0;
            }
        }
        named_bar(1, 128);
        for (int i = pt; i < 128 * 8; i += 128) cp16(sb + OFF_W2 + (i >> 3) * 144 + (i & 7) * 16, w2 + i * 8);
        cp_commit();
        cp_wait<0>();
    } else {
        const int Ls = lm.L0 + (strm < lm.rem ? 1 : 0);
        uint32_t acc[16], s[8], q[8];
#pragma unroll
        for (int i = 0; i < 16; i++) acc[i] = 0;
#pragma unroll
        for (int i = 0; i < 8; i++) { s[i] = 0; q[i] = 0; }
#pragma unroll
        for (int i = 0; i < 5; i++) fence_regs(w[i]);
        fence_regs(acc);
        const uint32_t qbase = sb + OFF_QH + hh * ROWS * 128;
        const uint32_t qch = wq * 2 + ((lane >> 3) & 1);
        const uint32_t lox = ((sb + OFF_XR) >> 4) | 0x10000, loe = ((sb + OFF_ER) >> 4) | 0x10000;
        const uint32_t madr = sb + OFF_MR + (lane & 3) * 32;
        uint32_t prev = 0;
        auto rowaddr = [&](uint32_t b, int gg) -> uint32_t {
            uint32_t row = (b & 32) ? 192 + (strm * 4 + gg) * 8 + (lane & 7) : lds8(sb + OFF_NOD + (b - 1) * 8 + (lane & 7));
            return qbase + row * 128 + ((qch ^ (row & 7)) << 4);
        };
        int st = strm, ph = 0;
        uint32_t eva = sb + OFF_EV + strm * 4;
        for (int t = 0; t < Ls; t++) {
            mbar_wait(bar_full + st * 8, ph);
            wg_fence();
            mma64h<0, HI128>(acc, w[0], lox + st * 512);
            mma64h<1, HI128>(acc, w[1], lox + st * 512 + 2);
            mma64h<1, HI128>(acc, w[2], lox + st * 512 + 4);
            mma64h<1, HI128>(acc, w[3], lox + st * 512 + 6);
            mma64h<1, HI32>(acc, w[4], loe + st * 128);
            wg_commit();
            uint32_t ev = lds32(eva);
            uint4 m0 = lds128(madr + st * 128), m1 = lds128(madr + st * 128 + 16);
            if (ev) {
#pragma unroll
                for (int gg = 0; gg < 4; gg++) {
                    uint32_t b = (ev >> (8 * gg)) & 255;
                    if (b) {
                        uint32_t pb = (prev >> (8 * gg)) & 255;
                        if (pb) stsm2t(rowaddr(pb, gg), s[2 * gg], s[2 * gg + 1]);
                        ldsm2t(q[2 * gg], q[2 * gg + 1], rowaddr(b & 31, gg));
                        s[2 * gg] = 0; s[2 * gg + 1] = 0;
                        prev = (prev & ~(255u << (8 * gg))) | (b << (8 * gg));
                    }
                }
            }
            wg_wait0();
            fence_regs(acc);
            if (lane == 0) mbar_arrive(bar_empty + st * 8);
            const uint32_t m[8] = {m0.x, m0.y, m0.z, m0.w, m1.x, m1.y, m1.z, m1.w};
#pragma unroll
            for (int i = 0; i < 16; i++) {
                const int si = ((i >> 1) & 3) * 2 + (i & 1);
                uint32_t u = hadd2(acc[i], q[si]);
                uint32_t h = hfma2(u, htanh2(u), u);
                s[si] = hfma2(h, m[i >> 1], s[si]);
            }
            eva += NS * 4;
            st += NS;
            if (st >= R) { st -= R; ph ^= 1; }
        }
#pragma unroll
        for (int gg = 0; gg < 4; gg++) {
            uint32_t pb = (prev >> (8 * gg)) & 255;
            if (pb & 32) stsm2t(rowaddr(pb, gg), s[2 * gg], s[2 * gg + 1]);
        }
        named_bar(2, NCW * 128);
#pragma unroll
        for (int gg = 0; gg < 4; gg++) {
            uint32_t pb = (prev >> (8 * gg)) & 255;
            if (pb && !(pb & 32)) {
                for (int g2 = strm * 4 + gg + 1; g2 < G; g2++) {
                    if (lds8(sb + OFF_EV + g2) != (pb | 32)) break;
                    uint32_t row = 192 + g2 * 8 + (lane & 7), a0, a1;
                    ldsm2t(a0, a1, qbase + row * 128 + ((qch ^ (row & 7)) << 4));
                    s[2 * gg] = hadd2(s[2 * gg], a0); s[2 * gg + 1] = hadd2(s[2 * gg + 1], a1);
                }
                stsm2t(rowaddr(pb, gg), s[2 * gg], s[2 * gg + 1]);
            }
        }
        proxy_fence();
    }
    __syncthreads();

    int bad = 0;
    if (wg < NCW) {
        uint32_t a2[8][4];
        const uint32_t wa = sb + OFF_W2 + (((lane >> 4) & 1) * 8 + (lane & 7)) * 144 + (wq * 16 + ((lane >> 3) & 1) * 8) * 2;
#pragma unroll
        for (int i = 0; i < 8; i++) {
            ldsm4t(a2[i], wa + i * 16 * 144);
#pragma unroll
            for (int j = 0; j < 4; j++) a2[i][j] = bf2h(a2[i][j]);
        }
        const float bo0 = bf2f(b2 + wq * 16 + (lane >> 2)), bo1 = bf2f(b2 + wq * 16 + 8 + (lane >> 2));
        for (int u = wg; u < 6; u += NCW) {
            float d[16];
#pragma unroll
            for (int i = 0; i < 16; i++) d[i] = 0.f;
#pragma unroll
            for (int i = 0; i < 8; i++) fence_regs(a2[i]);
            fence_regs(d);
            const uint32_t lo = ((sb + OFF_QH + u * 4096) >> 4) | 0x10000;
            wg_fence();
            mma32f<0>(d, a2[0], lo);
#pragma unroll
            for (int i = 1; i < 8; i++) mma32f<1>(d, a2[i], lo + (i >> 2) * (ROWS * 8) + (i & 3) * 2);
            wg_commit();
            wg_wait0();
            fence_regs(d);
            uint32_t r[8];
#pragma unroll
            for (int j = 0; j < 4; j++) {
                uint2 kk = lds64(sb + OFF_KEY + (u * 32 + j * 8 + (lane & 3) * 2) * 4);
                float g0 = (float)(kk.x >> 8), g1 = (float)(kk.y >> 8);
                float v0 = g0 > 0.f ? fmaf(g0, bo0, d[4 * j]) : 0.f, v1 = g1 > 0.f ? fmaf(g1, bo0, d[4 * j + 1]) : 0.f;
                float v2 = g0 > 0.f ? fmaf(g0, bo1, d[4 * j + 2]) : 0.f, v3 = g1 > 0.f ? fmaf(g1, bo1, d[4 * j + 3]) : 0.f;
                bad |= !(fabsf(v0) + fabsf(v1) + fabsf(v2) + fabsf(v3) < 3.0e38f);
                r[2 * j] = pack_b2(v0, v1); r[2 * j + 1] = pack_b2(v2, v3);
            }
#pragma unroll
            for (int j = 0; j < 4; j += 2) {
                int row = u * 32 + (j + (lane >> 4)) * 8 + (lane & 7);
                stsm4t(sb + OFF_OUT + row * 128 + (((wq * 2 + ((lane >> 3) & 1)) ^ (row & 7)) << 4), r[2 * j], r[2 * j + 1], r[2 * j + 2], r[2 * j + 3]);
            }
        }
    }
    if (__syncthreads_or(bad)) { slow_path(sp, x, ea, w1, b1, w2, b2, out); return; }
    for (int i = tid; i < nrows * 8; i += NT) {
        int row = i >> 3, ch = i & 7;
        ((uint4*)out)[cta * NPC * 8 + i] = lds128(sb + OFF_OUT + row * 128 + ((ch ^ (row & 7)) << 4));
    }
}

}

extern "C" void kernel_launch(void* const* d_in, const int* in_sizes, int n_in, void* d_out, int out_size) {
    static int coresident = -1;
    if (coresident < 0) {
        cudaFuncSetAttribute(mpnn_kernel, cudaFuncAttributeMaxDynamicSharedMemorySize, SMEM_BYTES);
        int dev = 0, sms = 0, nb = 0;
        cudaGetDevice(&dev);
        cudaDeviceGetAttribute(&sms, cudaDevAttrMultiProcessorCount, dev);
        cudaOccupancyMaxActiveBlocksPerMultiprocessor(&nb, mpnn_kernel, NT, SMEM_BYTES);
        coresident = (sms * nb >= NCTA) ? 1 : 0;
    }
    const __nv_bfloat16* x = (const __nv_bfloat16*)d_in[0];
    const __nv_bfloat16* ea = (const __nv_bfloat16*)d_in[1];
    const int* src = (const int*)d_in[2];
    const int* dst = (const int*)d_in[3];
    const __nv_bfloat16* w1 = (const __nv_bfloat16*)d_in[4];
    const __nv_bfloat16* b1 = (const __nv_bfloat16*)d_in[5];
    const __nv_bfloat16* w2 = (const __nv_bfloat16*)d_in[6];
    const __nv_bfloat16* b2 = (const __nv_bfloat16*)d_in[7];
    __nv_bfloat16* out = (__nv_bfloat16*)d_out;
    if (coresident) {
        mpnn_kernel<<<NCTA, NT, SMEM_BYTES>>>(x, ea, src, dst, w1, b1, w2, b2, out, 3);
    } else {
        mpnn_kernel<<<NCTA, NT, SMEM_BYTES>>>(x, ea, src, dst, w1, b1, w2, b2, out, 1);
        mpnn_kernel<<<NCTA, NT, SMEM_BYTES>>>(x, ea, src, dst, w1, b1, w2, b2, out, 2);
    }
}
```

```cpp
#include <cuda_runtime.h>
#include <cuda_bf16.h>
#include <cuda_fp16.h>
#include <stdint.h>

namespace {

constexpr int N_NODES = 25000;
constexpr int N_EDGES = 800000;
constexpr int NCTA = 132;
constexpr int NPC = 190;
constexpr int NT = 640;
constexpr int NP = 608;
constexpr int CHUNK = 6060;
constexpr int R = 8;
#define W1POS 3
#define ROT 7
#define FENCE 1
#define XPOS 1
#define PDV 5
constexpr int PD = PDV;
constexpr int LMAX = 56;
constexpr int CAP = 91;
constexpr int SPITCH = 752;
constexpr int GPITCH = 48;
constexpr int OVFCAP = 256;
constexpr uint32_t TAGMOD = (1u << 24) - 1;
constexpr int SPIN = 1 << 16;
#define MBSPIN (1 << 22)

constexpr uint32_t SB = 1024;
constexpr uint32_t A_XR = SB;
constexpr uint32_t A_ER = A_XR + R * 8192;
constexpr uint32_t A_MR = A_ER + R * 2048;
constexpr uint32_t A_QH = A_MR + 2048;
constexpr uint32_t A_TAB = A_QH + 2 * 32768;
constexpr uint32_t A_CNT = A_TAB + LMAX * 1024 + 64;
constexpr uint32_t A_KEY = A_CNT + 136 * 4;
constexpr uint32_t A_HIST = A_KEY + 196 * 4;
constexpr uint32_t A_LEN = A_HIST + 32 * 4;
constexpr uint32_t A_EV = A_LEN + 32 * 4;
constexpr uint32_t A_MISC = A_EV + (LMAX + 2) * 8;
constexpr uint32_t A_ZEND = A_MISC + 32;
constexpr uint32_t A_FIRST = A_ZEND;
constexpr uint32_t A_TAG = A_FIRST + 8;
constexpr uint32_t A_INFO = A_FIRST + 16;
constexpr uint32_t A_NOD = A_INFO + 196 * 4;
constexpr uint32_t A_POS = A_NOD + 192 * 4;
constexpr uint32_t A_MT = A_POS + 192;
constexpr uint32_t A_B2 = A_MT + 64 * 4;
constexpr uint32_t A_OVF = A_B2 + 128;
constexpr uint32_t A_BAR = A_OVF + OVFCAP * 8;
constexpr uint32_t A_END = A_BAR + 2 * R * 8;
constexpr int SMEM_BYTES = A_END - SB;
constexpr uint32_t A_STG = A_XR;
constexpr uint32_t A_W1 = SB + 98 * 1024;
constexpr uint32_t A_XO = A_XR + 5 * 8192;
constexpr uint32_t A_W2 = A_TAB;
constexpr uint32_t A_OUT = A_XR;
static_assert(A_STG + (NCTA + 1) * SPITCH <= A_W1, "alias");
static_assert(A_W1 + 145 * 272 <= A_TAB, "alias");
static_assert(A_QH % 1024 == 0 && A_TAB % 1024 == 0, "align");
static_assert(A_CNT % 16 == 0 && A_ZEND % 16 == 0 && A_B2 % 16 == 0 && A_OVF % 8 == 0 && A_BAR % 8 == 0 && A_NOD % 8 == 0 && A_EV % 8 == 0 && A_MISC % 16 == 0, "align");
static_assert(SMEM_BYTES <= 232448 && PD >= 3 && PD <= 6, "smem");

__device__ uint4 g_ent[NCTA * NCTA * GPITCH];
__device__ uint4 g_x16[(N_NODES + 1) * 8];
__device__ uint4 g_flag[NCTA * 40];
__device__ uint32_t g_cnt;

#define TC(i)
#define TS(i)
#define TW(i)
#define TWD(i, v)
#define TSX(i, cond)

__device__ __forceinline__ void wg_fence() { asm volatile("wgmma.fence.sync.aligned;" ::: "memory"); }
__device__ __forceinline__ void wg_commit() { asm volatile("wgmma.commit_group.sync.aligned;" ::: "memory"); }
__device__ __forceinline__ void wg_wait0() { asm volatile("wgmma.wait_group.sync.aligned 0;" ::: "memory"); }
template <int M> __device__ __forceinline__ void fence_regs(uint32_t (&d)[M]) {
#pragma unroll
    for (int i = 0; i < M; i++) asm volatile("" : "+r"(d[i])::"memory");
}
template <int M> __device__ __forceinline__ void fence_regs(float (&d)[M]) {
#pragma unroll
    for (int i = 0; i < M; i++) asm volatile("" : "+f"(d[i])::"memory");
}
constexpr uint32_t HI128 = 0x40000040;
constexpr uint32_t HI32 = 0xC0000010;
template <int SC, uint32_t HI>
__device__ __forceinline__ void mma64h(uint32_t (&d)[16], const uint32_t (&a)[4], uint32_t lo) {
    asm volatile("{\n.reg .pred p;\n.reg .b64 dsc;\nsetp.ne.b32 p, %21, 0;\nmov.b64 dsc, {%20, %22};\n"
        "wgmma.mma_async.sync.aligned.m64n64k16.f16.f16.f16 {%0, %1, %2, %3, %4, %5, %6, %7, %8, %9, %10, %11, %12, %13, %14, %15}, {%16, %17, %18, %19}, dsc, p, 1, 1, 0;\n}\n"
        : "+r"(d[0]), "+r"(d[1]), "+r"(d[2]), "+r"(d[3]), "+r"(d[4]), "+r"(d[5]), "+r"(d[6]), "+r"(d[7]), "+r"(d[8]), "+r"(d[9]), "+r"(d[10]), "+r"(d[11]), "+r"(d[12]), "+r"(d[13]), "+r"(d[14]), "+r"(d[15])
        : "r"(a[0]), "r"(a[1]), "r"(a[2]), "r"(a[3]), "r"(lo), "n"(SC), "n"(HI));
}
template <int SC, uint32_t HI>
__device__ __forceinline__ void mma96h(uint32_t (&d)[24], const uint32_t (&a)[4], uint32_t lo) {
    asm volatile("{\n.reg .pred p;\n.reg .b64 dsc;\nsetp.ne.b32 p, %29, 0;\nmov.b64 dsc, {%28, %30};\n"
        "wgmma.mma_async.sync.aligned.m64n96k16.f16.f16.f16 {%0, %1, %2, %3, %4, %5, %6, %7, %8, %9, %10, %11, %12, %13, %14, %15, %16, %17, %18, %19, %20, %21, %22, %23}, {%24, %25, %26, %27}, dsc, p, 1, 1, 0;\n}\n"
        : "+r"(d[0]), "+r"(d[1]), "+r"(d[2]), "+r"(d[3]), "+r"(d[4]), "+r"(d[5]), "+r"(d[6]), "+r"(d[7]), "+r"(d[8]), "+r"(d[9]), "+r"(d[10]), "+r"(d[11]), "+r"(d[12]), "+r"(d[13]), "+r"(d[14]), "+r"(d[15]), "+r"(d[16]), "+r"(d[17]), "+r"(d[18]), "+r"(d[19]), "+r"(d[20]), "+r"(d[21]), "+r"(d[22]), "+r"(d[23])
        : "r"(a[0]), "r"(a[1]), "r"(a[2]), "r"(a[3]), "r"(lo), "n"(SC), "n"(HI));
}
template <int SC, uint32_t HI>
__device__ __forceinline__ void mma48f(float (&d)[24], const uint32_t (&a)[4], uint32_t lo) {
    asm volatile("{\n.reg .pred p;\n.reg .b64 dsc;\nsetp.ne.b32 p, %29, 0;\nmov.b64 dsc, {%28, %30};\n"
        "wgmma.mma_async.sync.aligned.m64n48k16.f32.f16.f16 {%0, %1, %2, %3, %4, %5, %6, %7, %8, %9, %10, %11, %12, %13, %14, %15, %16, %17, %18, %19, %20, %21, %22, %23}, {%24, %25, %26, %27}, dsc, p, 1, 1, 0;\n}\n"
        : "+f"(d[0]), "+f"(d[1]), "+f"(d[2]), "+f"(d[3]), "+f"(d[4]), "+f"(d[5]), "+f"(d[6]), "+f"(d[7]), "+f"(d[8]), "+f"(d[9]), "+f"(d[10]), "+f"(d[11]), "+f"(d[12]), "+f"(d[13]), "+f"(d[14]), "+f"(d[15]), "+f"(d[16]), "+f"(d[17]), "+f"(d[18]), "+f"(d[19]), "+f"(d[20]), "+f"(d[21]), "+f"(d[22]), "+f"(d[23])
        : "r"(a[0]), "r"(a[1]), "r"(a[2]), "r"(a[3]), "r"(lo), "n"(SC), "n"(HI));
}
__device__ __forceinline__ uint32_t hadd2(uint32_t a, uint32_t b) { uint32_t r; asm("add.rn.f16x2 %0, %1, %2;" : "=r"(r) : "r"(a), "r"(b)); return r; }
__device__ __forceinline__ uint32_t hfma2(uint32_t a, uint32_t b, uint32_t c) { uint32_t r; asm("fma.rn.f16x2 %0, %1, %2, %3;" : "=r"(r) : "r"(a), "r"(b), "r"(c)); return r; }
__device__ __forceinline__ uint32_t htanh2(uint32_t a) { uint32_t r; asm("tanh.approx.f16x2 %0, %1;" : "=r"(r) : "r"(a)); return r; }
__device__ __forceinline__ uint32_t pack_h2(float lo, float hi) { uint32_t r; asm("cvt.rn.f16x2.f32 %0, %1, %2;" : "=r"(r) : "f"(hi), "f"(lo)); return r; }
__device__ __forceinline__ uint32_t pack_b2(float lo, float hi) { uint32_t r; asm("cvt.rn.bf16x2.f32 %0, %1, %2;" : "=r"(r) : "f"(hi), "f"(lo)); return r; }
__device__ __forceinline__ uint32_t bf2h(uint32_t v) { return pack_h2(__uint_as_float(v << 16), __uint_as_float(v & 0xffff0000u)); }
__device__ __forceinline__ uint32_t bf2h_half(uint32_t v) { return pack_h2(0.5f * __uint_as_float(v << 16), 0.5f * __uint_as_float(v & 0xffff0000u)); }
__device__ __forceinline__ uint4 bf2h4(uint4 v) { return make_uint4(bf2h(v.x), bf2h(v.y), bf2h(v.z), bf2h(v.w)); }

__device__ __forceinline__ void cp16(uint32_t s, const void* g) { asm volatile("cp.async.cg.shared.global [%0], [%1], 16;" ::"r"(s), "l"(g) : "memory"); }
__device__ __forceinline__ void cp16z(uint32_t s, const void* g, bool ignore) {
    asm volatile("{\n.reg .pred p;\nsetp.ne.u32 p, %2, 0;\ncp.async.cg.shared.global [%0], [%1], 16, p;\n}" ::"r"(s), "l"(g), "r"((uint32_t)ignore) : "memory");
}
__device__ __forceinline__ void cp_commit() { asm volatile("cp.async.commit_group;" ::: "memory"); }
template <int N> __device__ __forceinline__ void cp_wait() { asm volatile("cp.async.wait_group %0;" ::"n"(N) : "memory"); }
__device__ __forceinline__ void bulk_g2s(uint32_t s, const void* g, uint32_t bytes, uint32_t bar) {
    asm volatile("cp.async.bulk.shared::cluster.global.mbarrier::complete_tx::bytes [%0], [%1], %2, [%3];" ::"r"(s), "l"(g), "r"(bytes), "r"(bar) : "memory");
}
__device__ __forceinline__ void l2_prefetch(const void* g, uint32_t bytes) { asm volatile("cp.async.bulk.prefetch.L2.global [%0], %1;" ::"l"(g), "r"(bytes) : "memory"); }
__device__ __forceinline__ void proxy_fence() { asm volatile("fence.proxy.async.shared::cta;" ::: "memory"); }
__device__ __forceinline__ bool mbar_try(uint32_t bar, uint32_t parity) {
    uint32_t ok;
    asm volatile("{\n.reg .pred p;\nmbarrier.try_wait.parity.shared::cta.b64 p, [%1], %2;\nselp.u32 %0, 1, 0, p;\n}" : "=r"(ok) : "r"(bar), "r"(parity) : "memory");
    return ok;
}
__device__ __forceinline__ void mbar_wait(uint32_t bar, uint32_t parity) {
    if (__builtin_expect(!mbar_try(bar, parity), 0))
        for (int it = 0; it < MBSPIN; it++) if (mbar_try(bar, parity)) break;
}
__device__ __forceinline__ void mbar_arrive(uint32_t bar) { asm volatile("mbarrier.arrive.shared::cta.b64 _, [%0];" ::"r"(bar) : "memory"); }
__device__ __forceinline__ uint32_t lds32(uint32_t a) { uint32_t r; asm volatile("ld.shared.u32 %0, [%1];" : "=r"(r) : "r"(a) : "memory"); return r; }
__device__ __forceinline__ uint32_t lds16(uint32_t a) { uint32_t r; asm volatile("ld.shared.u16 %0, [%1];" : "=r"(r) : "r"(a) : "memory"); return r; }
__device__ __forceinline__ uint32_t lds8(uint32_t a) { uint32_t r; asm volatile("ld.shared.u8 %0, [%1];" : "=r"(r) : "r"(a) : "memory"); return r; }
__device__ __forceinline__ uint2 lds64(uint32_t a) { uint2 r; asm volatile("ld.shared.v2.u32 {%0,%1}, [%2];" : "=r"(r.x), "=r"(r.y) : "r"(a) : "memory"); return r; }
__device__ __forceinline__ uint4 lds128(uint32_t a) { uint4 r; asm volatile("ld.shared.v4.u32 {%0,%1,%2,%3}, [%4];" : "=r"(r.x), "=r"(r.y), "=r"(r.z), "=r"(r.w) : "r"(a) : "memory"); return r; }
__device__ __forceinline__ void sts128(uint32_t a, uint4 v) { asm volatile("st.shared.v4.u32 [%0], {%1,%2,%3,%4};" ::"r"(a), "r"(v.x), "r"(v.y), "r"(v.z), "r"(v.w) : "memory"); }
__device__ __forceinline__ void sts64(uint32_t a, uint32_t x, uint32_t y) { asm volatile("st.shared.v2.u32 [%0], {%1,%2};" ::"r"(a), "r"(x), "r"(y) : "memory"); }
__device__ __forceinline__ void sts32(uint32_t a, uint32_t v) { asm volatile("st.shared.u32 [%0], %1;" ::"r"(a), "r"(v) : "memory"); }
__device__ __forceinline__ void sts16(uint32_t a, uint32_t v) { asm volatile("st.shared.u16 [%0], %1;" ::"r"(a), "r"(v) : "memory"); }
__device__ __forceinline__ void sts8(uint32_t a, uint32_t v) { asm volatile("st.shared.u8 [%0], %1;" ::"r"(a), "r"(v) : "memory"); }
__device__ __forceinline__ uint32_t atoms_inc(uint32_t a) { uint32_t r; asm volatile("atom.shared.add.u32 %0, [%1], 1;" : "=r"(r) : "r"(a) : "memory"); return r; }
__device__ __forceinline__ void atoms_inc_if(uint32_t& r, uint32_t a, bool p) {
    asm volatile("{\n.reg .pred p;\nsetp.ne.u32 p, %2, 0;\n@p atom.shared.add.u32 %0, [%1], 1;\n}" : "+r"(r) : "r"(a), "r"((uint32_t)p) : "memory");
}
__device__ __forceinline__ void reds_max(uint32_t a, uint32_t v) { asm volatile("red.shared.max.u32 [%0], %1;" ::"r"(a), "r"(v) : "memory"); }
__device__ __forceinline__ uint32_t ldg_rlx32(const void* p) { uint32_t r; asm volatile("ld.relaxed.gpu.global.u32 %0, [%1];" : "=r"(r) : "l"(p) : "memory"); return r; }
__device__ __forceinline__ int2 ldg_nc64(const void* p) { int2 r; asm volatile("ld.global.nc.v2.u32 {%0,%1}, [%2];" : "=r"(r.x), "=r"(r.y) : "l"(p)); return r; }
__device__ __forceinline__ uint4 ldg_nc128(const void* p) { uint4 r; asm volatile("ld.global.nc.v4.u32 {%0,%1,%2,%3}, [%4];" : "=r"(r.x), "=r"(r.y), "=r"(r.z), "=r"(r.w) : "l"(p)); return r; }
__device__ __forceinline__ uint2 ldg_rlx64(const void* p) {
    uint2 r;
    asm volatile("{\n.reg .b64 a;\nld.relaxed.gpu.global.b64 a, [%2];\nmov.b64 {%0,%1}, a;\n}" : "=r"(r.x), "=r"(r.y) : "l"(p) : "memory");
    return r;
}
__device__ __forceinline__ uint4 ldg_rlx128_if(const void* p, bool on) {
    uint4 r;
    asm volatile("{\n.reg .pred p;\n.reg .b64 a, b;\nsetp.ne.u32 p, %5, 0;\n@p ld.relaxed.gpu.global.v2.b64 {a, b}, [%4];\nmov.b64 {%0,%1}, a;\nmov.b64 {%2,%3}, b;\n}"
                 : "=r"(r.x), "=r"(r.y), "=r"(r.z), "=r"(r.w) : "l"(p), "r"((uint32_t)on) : "memory");
    return r;
}
__device__ __forceinline__ uint4 ldg_l1_128_if(const void* p, bool on) {
    uint4 r;
    asm volatile("{\n.reg .pred p;\n.reg .b64 a, b;\nsetp.ne.u32 p, %5, 0;\n@p ld.relaxed.cta.global.v2.b64 {a, b}, [%4];\nmov.b64 {%0,%1}, a;\nmov.b64 {%2,%3}, b;\n}"
                 : "=r"(r.x), "=r"(r.y), "=r"(r.z), "=r"(r.w) : "l"(p), "r"((uint32_t)on) : "memory");
    return r;
}
__device__ __forceinline__ void stg_rlx32(void* p, uint32_t v) { asm volatile("st.relaxed.gpu.global.u32 [%0], %1;" ::"l"(p), "r"(v) : "memory"); }
__device__ __forceinline__ void stg_rlx128(void* p, uint4 v) {
    asm volatile("{\n.reg .b64 a, b;\nmov.b64 a, {%1,%2};\nmov.b64 b, {%3,%4};\nst.relaxed.gpu.global.v2.b64 [%0], {a, b};\n}" ::"l"(p), "r"(v.x), "r"(v.y), "r"(v.z), "r"(v.w) : "memory");
}
__device__ __forceinline__ void ldsm4t(uint32_t (&r)[4], uint32_t a) {
    asm volatile("ldmatrix.sync.aligned.m8n8.x4.trans.shared.b16 {%0,%1,%2,%3}, [%4];" : "=r"(r[0]), "=r"(r[1]), "=r"(r[2]), "=r"(r[3]) : "r"(a) : "memory");
}
__device__ __forceinline__ void ldsm2t(uint32_t& r0, uint32_t& r1, uint32_t a) {
    asm volatile("ldmatrix.sync.aligned.m8n8.x2.trans.shared.b16 {%0,%1}, [%2];" : "=r"(r0), "=r"(r1) : "r"(a) : "memory");
}
__device__ __forceinline__ void stsm2t(uint32_t a, uint32_t r0, uint32_t r1) {
    asm volatile("stmatrix.sync.aligned.m8n8.x2.trans.shared.b16 [%0], {%1,%2};" ::"r"(a), "r"(r0), "r"(r1) : "memory");
}
__device__ __forceinline__ void stsm4t(uint32_t a, uint32_t r0, uint32_t r1, uint32_t r2, uint32_t r3) {
    asm volatile("stmatrix.sync.aligned.m8n8.x4.trans.shared.b16 [%0], {%1,%2,%3,%4};" ::"r"(a), "r"(r0), "r"(r1), "r"(r2), "r"(r3) : "memory");
}
template <int ID, int N> __device__ __forceinline__ void bar_sync() { asm volatile("bar.sync %0, %1;" ::"n"(ID), "n"(N) : "memory"); }
template <int ID, int N> __device__ __forceinline__ void bar_arrive() { asm volatile("bar.arrive %0, %1;" ::"n"(ID), "n"(N) : "memory"); }
__device__ __forceinline__ uint32_t scan_up(uint32_t v) {
#pragma unroll
    for (int o = 1; o < 32; o <<= 1)
        asm volatile("{\n.reg .pred p;\n.reg .u32 t;\nshfl.sync.up.b32 t|p, %0, %1, 0, -1;\n@p add.u32 %0, %0, t;\n}" : "+r"(v) : "r"(o));
    return v;
}
__device__ __forceinline__ uint32_t scan_down(uint32_t v) {
#pragma unroll
    for (int o = 1; o < 32; o <<= 1)
        asm volatile("{\n.reg .pred p;\n.reg .u32 t;\nshfl.sync.down.b32 t|p, %0, %1, 31, -1;\n@p add.u32 %0, %0, t;\n}" : "+r"(v) : "r"(o));
    return v;
}
__device__ __forceinline__ float bf2f(const __nv_bfloat16* p) { return __bfloat162float(*p); }

__device__ __forceinline__ int chunk_start(int c) { return c * CHUNK + min(c, 40) * 2; }
static_assert(NCTA * CHUNK + 80 == N_EDGES && CHUNK / 2 + 1 <= 5 * NP && CHUNK / 2 >= 4 * NP, "chunks");

__device__ __noinline__ void slow_path(uint8_t* sp, const __nv_bfloat16* x, const __nv_bfloat16* ea, const int* src, const int* dst,
                                       const __nv_bfloat16* w1, const __nv_bfloat16* b1, const __nv_bfloat16* w2,
                                       const __nv_bfloat16* b2, __nv_bfloat16* out) {
    const int tid = threadIdx.x, lane = tid & 31, warp = tid >> 5, cta = blockIdx.x;
    const int nrows = min(NPC, N_NODES - cta * NPC);
    float* hs = (float*)sp;
    __nv_bfloat16* w1s = (__nv_bfloat16*)(sp + 192 * 128 * 4);
    int* dg = (int*)(sp + 192 * 128 * 4 + 144 * 128 * 2);
    __syncthreads();
    for (int i = tid; i < 192 * 128; i += NT) hs[i] = 0.f;
    for (int i = tid; i < 144 * 128; i += NT) w1s[i] = w1[i];
    for (int i = tid; i < 192; i += NT) dg[i] = 0;
    __syncthreads();
    float bb[4];
    for (int j = 0; j < 4; j++) bb[j] = bf2f(b1 + lane * 4 + j);
    for (int i0 = warp * 32; i0 < N_EDGES; i0 += NT) {
        const int mine = dst[i0 + lane] - cta * NPC;
        uint32_t hit = __ballot_sync(0xffffffffu, (unsigned)mine < (unsigned)nrows);
        while (hit) {
            const int b = __ffs(hit) - 1;
            hit &= hit - 1;
            const int eid = i0 + b, dl = __shfl_sync(0xffffffffu, mine, b), s = src[eid];
            float v[5];
            v[0] = bf2f(x + s * 64 + lane); v[1] = bf2f(x + s * 64 + 32 + lane);
            v[2] = bf2f(x + (cta * NPC + dl) * 64 + lane); v[3] = bf2f(x + (cta * NPC + dl) * 64 + 32 + lane);
            v[4] = lane < 16 ? bf2f(ea + (size_t)eid * 16 + lane) : 0.f;
            float z[4] = {bb[0], bb[1], bb[2], bb[3]};
#pragma unroll
            for (int c = 0; c < 5; c++) {
                for (int kk = 0; kk < (c == 4 ? 16 : 32); kk++) {
                    float a = __shfl_sync(0xffffffffu, v[c], kk);
                    const __nv_bfloat16* wr = w1s + (c * 32 + kk) * 128 + lane * 4;
#pragma unroll
                    for (int j = 0; j < 4; j++) z[j] = fmaf(a, __bfloat162float(wr[j]), z[j]);
                }
            }
#pragma unroll
            for (int j = 0; j < 4; j++) atomicAdd(&hs[dl * 128 + lane * 4 + j], z[j] / (1.f + expf(-z[j])));
            if (lane == 0) atomicAdd(&dg[dl], 1);
        }
    }
    __syncthreads();
    for (int i = tid; i < nrows * 64; i += NT) {
        int n = i >> 6, d = i & 63;
        float a = 0.f;
        if (dg[n] > 0) {
            a = (float)dg[n] * bf2f(b2 + d);
            for (int h = 0; h < 128; h++) a = fmaf(hs[n * 128 + h], bf2f(w2 + h * 64 + d), a);
        }
        out[(size_t)(cta * NPC + n) * 64 + d] = __float2bfloat16(a);
    }
}

__global__ void __launch_bounds__(NT, 1)
mpnn_kernel(const __nv_bfloat16* __restrict__ x, const __nv_bfloat16* __restrict__ ea, const int* __restrict__ src,
            const int* __restrict__ dst, const __nv_bfloat16* __restrict__ w1, const __nv_bfloat16* __restrict__ b1,
            const __nv_bfloat16* __restrict__ w2, const __nv_bfloat16* __restrict__ b2, __nv_bfloat16* __restrict__ out) {
    extern __shared__ uint8_t smem_raw[];
    const int tid = threadIdx.x, lane = tid & 31;
    __builtin_assume(tid < NT);
    const int warp = __shfl_sync(0xffffffffu, tid >> 5, 0);
    const int cta = blockIdx.x;
    const int nrows = min(NPC, N_NODES - cta * NPC);
    const int e0 = chunk_start(cta);
    const int nv2 = CHUNK / 2 + (cta < 40);
    if ((uint32_t)__cvta_generic_to_shared(smem_raw) != SB) { slow_path(smem_raw, x, ea, src, dst, w1, b1, w2, b2, out); return; }
    constexpr uint32_t bar_full = A_BAR, bar_empty = A_BAR + R * 8;

    TS(0);
    int2 d2[5];
    if (warp < 19) {
        d2[4] = make_int2(NCTA * NPC, NCTA * NPC);
#pragma unroll
        for (int r = 0; r < 5; r++) if (r < 4 || r * NP + tid < nv2) d2[r] = ldg_nc64((const int2*)(dst + e0) + r * NP + tid);
        {
            const int c = warp * 7 + (lane >> 1);
            if (lane < 14 && c < NCTA) stg_rlx128(g_ent + (c * NCTA + cta) * GPITCH + (lane & 1), make_uint4(0, 0, 0, 0));
        }
        if (tid < (int)(A_ZEND - A_CNT) / 16) sts128(A_CNT + tid * 16, make_uint4(0, 0, 0, 0));
        if (tid >= 256 && tid < 256 + 64) { const uint32_t l = tid - 255; sts32(A_MT + (tid - 256) * 4, 0xffffffffu / (l * 1024) + 1); }
        if (tid == 320) sts64(A_FIRST, 0x60606060u, 0x60606060u);
    } else {
        if (lane == 0) {
            const uint32_t cnt0 = ldg_rlx32(&g_cnt);
#pragma unroll
            for (int i = 0; i < 2 * R; i++) asm volatile("mbarrier.init.shared::cta.b64 [%0], %1;" ::"r"(A_BAR + i * 8), "r"(i < R ? 4 : 8) : "memory");
            sts32(A_TAG, (cnt0 / NCTA + 1) << 8);
        }
    }
    int2 s2[5];
    if (warp < 19) {
#pragma unroll
        for (int r = 0; r < 5; r++) if (r < 4 || r * NP + tid < nv2) s2[r] = ldg_nc64((const int2*)(src + e0) + r * NP + tid);
    }
    __syncthreads();
    TS(1);
    const uint32_t tagw = lds32(A_TAG);
    uint4 xr[3];
    auto load_w = [&]() {
        int i = (cta * ROT) % 72;
#pragma unroll 4
        for (int n = 0; n < 72; n++) {
            cp16(A_W1 + (i * 2 + (lane >> 4)) * 272 + (lane & 15) * 16, (const uint4*)w1 + i * 32 + lane);
            i = i == 71 ? 0 : i + 1;
        }
        if (lane < 16) cp16(A_W1 + 144 * 272 + lane * 16, (const uint4*)b1 + lane);
        else if (lane < 24) cp16(A_B2 + (lane - 16) * 16, (const uint4*)b2 + lane - 16);
        if (lane == 0) l2_prefetch(w2, 128 * 64 * 2);
        TSX(15, lane == 0);
    };

    if (warp < 19) {
        uint32_t c[10], rk[10];
#pragma unroll
        for (int i = 0; i < 10; i++) {
            c[i] = __umulhi(i & 1 ? d2[i >> 1].y : d2[i >> 1].x, 44151u << 9);
            rk[i] = atoms_inc(A_CNT + c[i] * 4);
        }
#pragma unroll
        for (int r = 0; r < 3; r++) {
            xr[r] = make_uint4(0, 0, 0, 0);
            if (r * NP + tid < nrows * 8) xr[r] = ldg_nc128((const uint4*)x + cta * NPC * 8 + r * NP + tid);
        }
        TS(2);
#pragma unroll
        for (int i = 0; i < 10; i++)
            sts64(A_STG + 8 + c[i] * SPITCH + min(rk[i], (uint32_t)CAP) * 8,
                  (uint32_t)(i & 1 ? s2[i >> 1].y : s2[i >> 1].x) + ((((i >> 1) * NP + tid) * 2 + (i & 1)) << 15),
                  (i & 1 ? d2[i >> 1].y : d2[i >> 1].x) + tagw - c[i] * NPC);
    } else {
#pragma unroll
        for (int j = 0; j < 5; j++)
            if (j * 32 + lane < NCTA) stg_rlx32((uint32_t*)(g_flag + (j * 32 + lane) * 40) + cta, 0);
        if (lane == 0) stg_rlx128(g_flag + cta * 40 + 33, make_uint4(0, 0, 0, 0));
        if (W1POS == 0) load_w();
    }
    __syncthreads();
    TS(3);
    if (warp < 19) {
        const int c0 = warp * 7;
        const uint32_t cl = lds32(A_CNT + (c0 + (lane & 7)) * 4);
        uint4* gp = g_ent + (c0 * NCTA + cta) * GPITCH + lane;
        const uint32_t sp = A_STG + c0 * SPITCH + lane * 16;
#pragma unroll
        for (int k = 0; k < 7; k++) {
            const uint32_t n = __shfl_sync(0xffffffffu, cl, k);
            if (k < 6 || warp < 18) {
                if ((uint32_t)(lane >> 1) * 4 <= n) {
                    uint4 v = lds128(sp + k * SPITCH);
                    if (lane == 0) { v.x = n; v.y = tagw; }
                    if (2u * lane > n) v.y = 0;
                    if (2u * lane >= n) v.w = 0;
                    stg_rlx128(gp + k * NCTA * GPITCH, v);
                }
                if (__builtin_expect(n >= 64, 0)) {
                    if (lane < 14 && 64 + (uint32_t)(lane >> 1) * 4 <= n) {
                        uint4 v = lds128(sp + k * SPITCH + 512);
                        if (64 + 2u * lane > n) v.y = 0;
                        if (64 + 2u * lane >= n) v.w = 0;
                        stg_rlx128(gp + k * NCTA * GPITCH + 32, v);
                    }
                }
            }
        }
        TS(4); TW(0);
#pragma unroll
        for (int r = 0; r < (LMAX * 64 + NP - 1) / NP; r++)
            if ((r + 1) * NP <= LMAX * 64 || r * NP + tid < LMAX * 64) sts128(A_TAB + (r * NP + tid) * 16, make_uint4(N_NODES, 0, N_NODES, 0));
    } else {
        if (W1POS == 1) load_w();
    }
    __syncthreads();
    TS(5);

    if (warp == 19) {
        if (lane == 0) asm volatile("red.relaxed.gpu.global.inc.u32 [%0], %1;" ::"l"(&g_cnt), "r"(NCTA * TAGMOD - 1) : "memory");
        if (W1POS == 2) load_w();
        bar_sync<11, NT>();
        TW(0);
        asm volatile("fence.acq_rel.gpu;" ::: "memory");
        TW(1);
#pragma unroll
        for (int j = 0; j < 5; j++)
            if (j * 32 + lane < NCTA) stg_rlx32((uint32_t*)(g_flag + (j * 32 + lane) * 40) + cta, tagw);
        TSX(16, lane == 0);
        if (W1POS == 3) load_w();
        bool ok = false;
        int nit = 0;
        for (int it = 0; it < SPIN && !ok; it++) {
            const uint4 f0 = ldg_rlx128_if(g_flag + cta * 40 + lane, true), f1 = ldg_rlx128_if(g_flag + cta * 40 + 32, true);
            ok = __all_sync(0xffffffffu, f0.x == tagw && f0.y == tagw && f0.z == tagw && f0.w == tagw && f1.x == tagw && f1.y == tagw && f1.z == tagw && f1.w == tagw);
            nit++;
        }
        TW(2);
        if (W1POS == 4) load_w();
        asm volatile("fence.acq_rel.gpu;" ::: "memory");
        TW(3);
        if (!ok) sts32(A_MISC + 4, 1);
        TSX(17, lane == 0);
        asm volatile("cp.async.wait_all;" ::: "memory");
        TSX(19, lane == 0);
    } else {
#pragma unroll
        for (int r = 0; r < 3; r++) {
            const int i = r * NP + tid, row = i >> 3;
            xr[r] = bf2h4(xr[r]);
            if (i < 192 * 8) sts128(A_XO + row * 128 + (((i ^ row) & 7) << 4), xr[r]);
        }
        const int p0 = warp * 7;
        const uint4* rp = g_ent + (cta * NCTA + p0) * GPITCH;
        int nl = -1;
        bool fail = false;
        if (lane < 7 && p0 + lane < NCTA) {
            uint2 h;
            int it = 0;
            do { h = ldg_rlx64(rp + lane * GPITCH); } while (h.y != tagw && ++it < SPIN);
            nl = h.x;
            if (h.y != tagw || nl > CAP) { fail = true; nl = -1; }
        }
        __syncwarp();
        TS(6); TW(1);
        rp += lane;
        uint4 en[7];
        int nk[7];
#pragma unroll
        for (int k = 0; k < 7; k++) {
            nk[k] = __shfl_sync(0xffffffffu, nl, k);
            en[k] = ldg_l1_128_if(rp + k * GPITCH, 2 * lane <= nk[k]);
        }
        uint32_t big = __ballot_sync(0xffffffffu, nl >= 64);
        uint4 ex;
        if (__builtin_expect(big != 0, 0)) {
            const int k = __ffs(big) - 1;
            ex = ldg_rlx128_if(rp + k * GPITCH + 32, 64 + 2 * lane <= __shfl_sync(0xffffffffu, nl, k));
        }
#pragma unroll
        for (int r = 0; r < 3; r++) if (r * NP + tid < nrows * 8) g_x16[cta * NPC * 8 + r * NP + tid] = xr[r];
        bar_arrive<11, NT>();
        TWD(2, en[0].x ^ en[1].x ^ en[2].x ^ en[3].x ^ en[4].x ^ en[5].x ^ en[6].x);
        uint32_t ka[14], rk[14];
        int nret = 0;
#pragma unroll
        for (int k = 0; k < 7; k++) {
            bool pa = 2 * lane <= nk[k], pb = 2 * lane < nk[k];
            uint32_t da = en[k].y - tagw, db = en[k].w - tagw;
            if (__builtin_expect((pa && da >= 256) || (pb && db >= 256), 0)) {
                bool bad = true;
                for (int it = 0; it < SPIN && bad; it++) {
                    en[k] = ldg_rlx128_if(rp + k * GPITCH, true);
                    nret++;
                    da = en[k].y - tagw; db = en[k].w - tagw;
                    bad = da >= 256 || (pb && db >= 256);
                }
                if (bad) { fail = true; pa = pb = false; }
            }
            pa = pa && lane > 0;
            ka[2 * k] = pa ? A_KEY + da * 4 : A_KEY + 192 * 4;
            ka[2 * k + 1] = pb ? A_KEY + db * 4 : A_KEY + 192 * 4;
            rk[2 * k] = 0; rk[2 * k + 1] = 0;
            atoms_inc_if(rk[2 * k], ka[2 * k], pa);
            atoms_inc_if(rk[2 * k + 1], ka[2 * k + 1], pb);
        }
        for (bool first = true; __builtin_expect(big != 0, 0); first = false) {
            const int k = __ffs(big) - 1;
            big &= big - 1;
            const int n = __shfl_sync(0xffffffffu, nl, k);
            if (64 + 2 * lane <= n) {
                const bool pb = 64 + 2 * lane < n;
                bool bad = true;
                for (int it = 0; it < SPIN; it++) {
                    if (it || !first) ex = ldg_rlx128_if(rp + k * GPITCH + 32, true);
                    bad = ex.y - tagw >= 256 || (pb && ex.w - tagw >= 256);
                    if (!bad) break;
                }
                if (bad) fail = true;
                else {
                    for (int j = 0; j < (pb ? 2 : 1); j++) {
                        const uint32_t a = j ? ex.z : ex.x, dl = (j ? ex.w : ex.y) - tagw;
                        const uint32_t r = atoms_inc(A_KEY + dl * 4), o = atoms_inc(A_MISC);
                        if (o < OVFCAP) sts64(A_OVF + o * 8, ((a >> 15) + chunk_start(p0 + k)) | (dl << 20), (a & 0x7fff) | (r << 15));
                    }
                }
            }
            __syncwarp();
        }
        TWD(3, rk[13] ^ rk[12]);
        if (fail) sts32(A_MISC + 4, 1);
        proxy_fence();
        bar_sync<1, NP>();
        TS(7);
        if (warp < 6) {
            const uint32_t deg = lds32(A_KEY + tid * 4), len = (deg + 1) >> 1, bin = min(len, 31u);
            const uint32_t r = atoms_inc(A_HIST + bin * 4);
            bar_sync<2, 192>();
            const uint32_t h = lds32(A_HIST + lane * 4);
            const uint32_t pos = __shfl_sync(0xffffffffu, scan_down(h) - h, bin) + r;
            reds_max(A_LEN + (pos >> 3) * 4, len);
            sts8(A_POS + tid, pos);
            sts32(A_NOD + pos * 4, tid | (deg << 8));
            bar_sync<2, 192>();
            const uint32_t l = lds32(A_LEN + lane * 4), inc = scan_up(l), start = inc - l;
            sts32(A_INFO + tid * 4, __shfl_sync(0xffffffffu, start, pos >> 3) * 1024 + (pos & 7) * 64);
            if (warp == 5) {
                const uint32_t L = max((__shfl_sync(0xffffffffu, inc, 31) + 7) >> 3, 1u);
                if (L > LMAX || lds32(A_MISC) > OVFCAP) sts32(A_MISC + 4, 1);
                else {
                    const uint32_t M = lds32(A_MT + L * 4 - 4);
                    if (lane == 0) { sts64(A_MISC + 8, M, L * 1024 - 8); sts32(A_MISC + 16, L); sts32(A_INFO + 192 * 4, L * 2048 - 8); }
                    if (l) {
                        uint32_t g = __umulhi(start * 1024, M);
                        const uint32_t t = start - g * L;
                        if (t) { sts8(A_EV + t * 8 + g, lane + 1); g++; }
                        for (; g * L < inc; g++) sts8(A_FIRST + g, g * L > start ? lane | 32 : lane);
                    }
                }
            }
        }
        uint32_t ts[14], te[14];
#pragma unroll
        for (int k = 0; k < 7; k++) {
            ts[2 * k] = en[k].x & 0x7fff; te[2 * k] = (en[k].x >> 15) + chunk_start(p0 + k);
            ts[2 * k + 1] = en[k].z & 0x7fff; te[2 * k + 1] = (en[k].z >> 15) + chunk_start(p0 + k);
        }
        fence_regs(ts); fence_regs(te);
        bar_sync<1, NP>();
        TS(8);
        const uint4 ms = lds128(A_MISC);
        if (!ms.y) {
#pragma unroll
            for (int i = 0; i < 14; i++) {
                const uint32_t a = lds32(ka[i] + (A_INFO - A_KEY)) + rk[i] * 512;
                sts64(A_TAB + a - __umulhi(a, ms.z) * ms.w, ts[i], te[i]);
            }
            for (uint32_t i = tid; i < ms.x; i += NP) {
                const uint2 t = lds64(A_OVF + i * 8);
                const uint32_t a = lds32(A_INFO + (t.x >> 20) * 4) + (t.y >> 15) * 512;
                sts64(A_TAB + a - __umulhi(a, ms.z) * ms.w, t.y & 0x7fff, t.x & 0xfffff);
            }
        }
    }
    __syncthreads();
    TS(9);
    if (lds32(A_MISC + 4)) { slow_path(smem_raw, x, ea, src, dst, w1, b1, w2, b2, out); return; }
    const int L = lds32(A_MISC + 16);

    const int wg = warp >> 2, wq = warp & 3;
    int bad = 0;
    if (wg == 4) {
        const int par = wq >> 1, cx = (wq & 1) * 4 + (lane >> 3), ce = (wq & 1) * 4 + ((lane >> 1) & 3), ge = lane >> 3;
        const uint32_t xdst = A_XR + (par * 32 + cx) * 128 + (((lane & 7) ^ cx) << 4);
        const uint32_t edst = A_ER + (par * 32 + ge * 8 + ce) * 32 + (((lane ^ wq) & 1) << 4);
        const uint32_t mdst = A_MR + (ce >> 1) * 32 + (par * 4 + ge) * 4 + (ce & 1) * 2;
        uint32_t tx = A_TAB + par * 512 + cx * 64, te = A_TAB + par * 512 + ce * 64 + ge * 8;
        const char* xg = (const char*)g_x16 + (lane & 7) * 16;
        const char* eg = (const char*)ea + (lane & 1) * 16;
        const int S = 2 * L;
        auto issue = [&](int k) {
            const int st = k & (R - 1);
            const uint4 a = lds128(tx), b = lds128(tx + 16);
            const uint2 e = lds64(te);
            const int inc = (k & 1) ? 1024 - 32 : 32;
            tx += inc; te += inc;
            mbar_wait(bar_empty + st * 8, ((k >> 3) & 1) ^ 1);
            cp16z(edst + st * 2048, eg + (size_t)e.y * 32, e.x == N_NODES);
            cp16(xdst + st * 8192, xg + (size_t)a.x * 128);
            cp16(xdst + st * 8192 + 1024, xg + (size_t)a.z * 128);
            cp16(xdst + st * 8192 + 2048, xg + (size_t)b.x * 128);
            cp16(xdst + st * 8192 + 3072, xg + (size_t)b.z * 128);
            sts16(mdst + st * 128, e.x == N_NODES ? 0 : 0x3c00);
        };
        auto finish = [&](int j) {
            const int sj = j & (R - 1);
            sts128(edst + sj * 2048, bf2h4(lds128(edst + sj * 2048)));
            proxy_fence();
            __syncwarp();
            if (lane == 0) mbar_arrive(bar_full + sj * 8);
        };
        for (int k = 0; k < 5; k++) {
            if (k < S) issue(k);
            cp_commit();
        }
        cp_wait<4>();
        finish(0);
        cp_wait<3>();
        finish(1);
        bar_sync<5, NT>();
        for (int k = 5; k < PD + 2; k++) {
            if (k < S) issue(k);
            cp_commit();
        }
        for (int k = PD + 2; k < S + PD; k++) {
            if (k < S) issue(k);
            cp_commit();
            cp_wait<PD>();
            finish(k - PD);
        }
        TSX(18, tid == 512);
        const int pt = tid - 512;
        uint4 v[8];
#pragma unroll
        for (int i = 0; i < 8; i++) v[i] = __ldg((const uint4*)w2 + i * 128 + pt);
        bar_sync<4, 128>();
#pragma unroll
        for (int i = 0; i < 8; i++) sts128(A_W2 + (i * 16 + (pt >> 3)) * 144 + (pt & 7) * 16, bf2h4(v[i]));
        bar_sync<3, NT>();
    } else {
        const int hh = wg & 1, strm = wg >> 1;
        uint32_t w[5][4];
        const uint32_t qch = wq * 2 + ((lane >> 3) & 1);
        {
            const int h0 = hh * 64 + wq * 16;
            const uint32_t wa = A_W1 + (((lane >> 4) & 1) * 8 + (lane & 7)) * 272 + (h0 + ((lane >> 3) & 1) * 8) * 2;
            uint32_t wb[4][4], acc[24];
#pragma unroll
            for (int i = 0; i < 4; i++) ldsm4t(wb[i], wa + (64 + i * 16) * 272);
#pragma unroll
            for (int i = 0; i < 4; i++) ldsm4t(w[i], wa + i * 16 * 272);
            ldsm4t(w[4], wa + 128 * 272);
            const uint32_t bl0 = lds16(A_W1 + 144 * 272 + (h0 + (lane >> 2)) * 2), bl1 = lds16(A_W1 + 144 * 272 + (h0 + 8 + (lane >> 2)) * 2);
#pragma unroll
            for (int i = 0; i < 4; i++)
#pragma unroll
                for (int j = 0; j < 4; j++) wb[i][j] = bf2h_half(wb[i][j]);
#pragma unroll
            for (int i = 0; i < 4; i++) fence_regs(wb[i]);
            const uint32_t lo = ((A_XO >> 4) | 0x10000) + strm * 768;
            wg_fence();
            mma96h<0, HI128>(acc, wb[0], lo);
            mma96h<1, HI128>(acc, wb[1], lo + 2);
            mma96h<1, HI128>(acc, wb[2], lo + 4);
            mma96h<1, HI128>(acc, wb[3], lo + 6);
            wg_commit();
#pragma unroll
            for (int i = 0; i < 5; i++)
#pragma unroll
                for (int j = 0; j < 4; j++) w[i][j] = bf2h_half(w[i][j]);
            const uint32_t bq0 = bf2h_half(bl0 * 0x10001u), bq1 = bf2h_half(bl1 * 0x10001u);
            uint32_t qa[6];
#pragma unroll
            for (int j = 0; j < 6; j++) {
                const uint32_t p = lds8(A_POS + strm * 96 + j * 16 + (lane >> 4) * 8 + (lane & 7));
                qa[j] = A_QH + hh * 32768 + p * 128 + ((qch ^ (p & 7)) << 4);
            }
            wg_wait0();
            fence_regs(acc);
            bar_arrive<5, NT>();
            bar_sync<6, 512>();
#pragma unroll
            for (int j = 0; j < 6; j++)
                stsm4t(qa[j], hadd2(acc[4 * j], bq0), hadd2(acc[4 * j + 1], bq1), hadd2(acc[4 * j + 2], bq0), hadd2(acc[4 * j + 3], bq1));
            bar_sync<6, 512>();
        }
        TS(10);
        const uint32_t ql = A_QH + hh * 32768 + (lane & 7) * 128 + ((qch ^ (lane & 7)) << 4);
        uint32_t acc[16], s[8], q[8], fa[4];
        {
            const uint32_t f = lds32(A_FIRST + strm * 4);
#pragma unroll
            for (int g = 0; g < 4; g++) {
                const uint32_t b = f >> (8 * g), a = ql + (b & 31) * 1024;
                ldsm2t(q[2 * g], q[2 * g + 1], a);
                fa[g] = (b & 32) ? ql + (24 + strm * 4 + g) * 1024 : a;
            }
        }
#pragma unroll
        for (int i = 0; i < 8; i++) s[i] = 0;
#pragma unroll
        for (int i = 0; i < 5; i++) fence_regs(w[i]);
        const uint32_t madr = A_MR + (lane & 3) * 32;
        uint32_t eva = A_EV + strm * 4;
        int kk = strm;
        auto gemm = [&](bool wt) {
            const uint32_t st = kk & (R - 1);
            if (wt) mbar_wait(bar_full + st * 8, (kk >> 3) & 1);
            constexpr uint32_t lox = (A_XR >> 4) | 0x10000, loe = (A_ER >> 4) | 0x10000;
            wg_fence();
            mma64h<0, HI128>(acc, w[0], lox + st * 512);
            mma64h<1, HI128>(acc, w[1], lox + st * 512 + 2);
            mma64h<1, HI128>(acc, w[2], lox + st * 512 + 4);
            mma64h<1, HI128>(acc, w[3], lox + st * 512 + 6);
            mma64h<1, HI32>(acc, w[4], loe + st * 128);
            wg_commit();
        };
        gemm(true);
        TS(11); TC(21);
        for (int t = L; t > 0; t--) {
            const uint32_t st = kk & (R - 1);
            const uint32_t ev = lds32(eva);
            const uint4 m0 = lds128(madr + st * 128), m1 = lds128(madr + st * 128 + 16);
            if (__builtin_expect(ev != 0, 0)) {
#pragma unroll
                for (int g = 0; g < 4; g++) {
                    const uint32_t b = (ev >> (8 * g)) & 255;
                    if (b) {
                        stsm2t(fa[g], s[2 * g], s[2 * g + 1]);
                        fa[g] = ql - 1024 + b * 1024;
                        ldsm2t(q[2 * g], q[2 * g + 1], fa[g]);
                        s[2 * g] = 0; s[2 * g + 1] = 0;
                    }
                }
            }
            wg_wait0();
            fence_regs(acc);
            const uint32_t m[8] = {m0.x, m0.y, m0.z, m0.w, m1.x, m1.y, m1.z, m1.w};
            uint32_t u[16];
#pragma unroll
            for (int i = 0; i < 16; i++) u[i] = hfma2(q[((i >> 1) & 3) * 2 + (i & 1)], m[i >> 1], acc[i]);
            fence_regs(u);
            if (lane == 0) mbar_arrive(bar_empty + st * 8);
            eva += 8;
            kk += 2;
            gemm(t > 1);
#pragma unroll
            for (int i = 0; i < 16; i++) {
                const int si = ((i >> 1) & 3) * 2 + (i & 1);
                s[si] = hadd2(s[si], hfma2(u[i], htanh2(u[i]), u[i]));
            }
        }
        wg_wait0();
        fence_regs(acc);
        TS(12); TC(22);
#pragma unroll
        for (int g = 0; g < 4; g++)
            if (fa[g] >= ql + 24 * 1024) stsm2t(fa[g], s[2 * g], s[2 * g + 1]);
        bar_sync<3, NT>();
#pragma unroll
        for (int g = 0; g < 4; g++) {
            if (fa[g] < ql + 24 * 1024) {
                const uint32_t b = ((fa[g] - ql) >> 10) | 32;
                for (int g2 = strm * 4 + g + 1; g2 < 8; g2++) {
                    if (lds8(A_FIRST + g2) != b) break;
                    uint32_t a0, a1;
                    ldsm2t(a0, a1, ql + (24 + g2) * 1024);
                    s[2 * g] = hadd2(s[2 * g], a0); s[2 * g + 1] = hadd2(s[2 * g + 1], a1);
                }
                stsm2t(fa[g], s[2 * g], s[2 * g + 1]);
            }
        }
        proxy_fence();
        uint32_t a2[8][4];
        const uint32_t wa = A_W2 + (((lane >> 4) & 1) * 8 + (lane & 7)) * 144 + qch * 16;
#pragma unroll
        for (int i = 0; i < 8; i++) ldsm4t(a2[i], wa + i * 16 * 144);
        const float bo0 = __uint_as_float(lds16(A_B2 + (wq * 16 + (lane >> 2)) * 2) << 16);
        const float bo1 = __uint_as_float(lds16(A_B2 + (wq * 16 + 8 + (lane >> 2)) * 2) << 16);
        float d[24];
#pragma unroll
        for (int i = 0; i < 8; i++) fence_regs(a2[i]);
        bar_sync<6, 512>();
        TS(13);
        const uint32_t lo = ((A_QH >> 4) | 0x10000) + wg * 384;
        wg_fence();
        mma48f<0, HI128>(d, a2[0], lo);
#pragma unroll
        for (int i = 1; i < 8; i++) mma48f<1, HI128>(d, a2[i], lo + (i >> 2) * 2048 + (i & 3) * 2);
        wg_commit();
        float dg[12];
#pragma unroll
        for (int j = 0; j < 6; j++) {
            const uint2 v = lds64(A_NOD + (wg * 48 + j * 8 + (lane & 3) * 2) * 4);
            dg[2 * j] = (float)(v.x >> 8); dg[2 * j + 1] = (float)(v.y >> 8);
        }
        wg_wait0();
        fence_regs(d);
        uint32_t r[12];
#pragma unroll
        for (int j = 0; j < 6; j++) {
            const float g0 = dg[2 * j], g1 = dg[2 * j + 1];
            const float v0 = g0 > 0.f ? fmaf(g0, bo0, d[4 * j]) : 0.f, v1 = g1 > 0.f ? fmaf(g1, bo0, d[4 * j + 1]) : 0.f;
            const float v2 = g0 > 0.f ? fmaf(g0, bo1, d[4 * j + 2]) : 0.f, v3 = g1 > 0.f ? fmaf(g1, bo1, d[4 * j + 3]) : 0.f;
            bad |= !(fabsf(v0) + fabsf(v1) + fabsf(v2) + fabsf(v3) < 3.0e38f);
            r[2 * j] = pack_b2(v0, v1); r[2 * j + 1] = pack_b2(v2, v3);
        }
        const uint32_t oa = A_OUT + (wg * 48 + (lane >> 4) * 8 + (lane & 7)) * 128 + ((qch ^ (lane & 7)) << 4);
#pragma unroll
        for (int j = 0; j < 3; j++) stsm4t(oa + j * 2048, r[4 * j], r[4 * j + 1], r[4 * j + 2], r[4 * j + 3]);
        asm volatile("bar.sync %0, 128;" ::"r"(7 + wg) : "memory");
#pragma unroll
        for (int j = 0; j < 3; j++) {
            const int row = wg * 48 + j * 16 + wq * 4 + (lane >> 3);
            const uint32_t n = lds8(A_NOD + row * 4);
            const uint4 v = lds128(A_OUT + row * 128 + (((lane ^ row) & 7) << 4));
            if ((int)n < nrows) ((uint4*)out)[(cta * NPC + n) * 8 + (lane & 7)] = v;
        }
    }
    TS(14);
    if (__syncthreads_or(bad)) slow_path(smem_raw, x, ea, src, dst, w1, b1, w2, b2, out);
}

}

extern "C" void kernel_launch(void* const* d_in, const int* in_sizes, int n_in, void* d_out, int out_size) {
    static bool init = false;
    if (!init) {
        cudaFuncSetAttribute(mpnn_kernel, cudaFuncAttributeMaxDynamicSharedMemorySize, SMEM_BYTES);
        init = true;
    }
    mpnn_kernel<<<NCTA, NT, SMEM_BYTES>>>((const __nv_bfloat16*)d_in[0], (const __nv_bfloat16*)d_in[1], (const int*)d_in[2], (const int*)d_in[3],
                                          (const __nv_bfloat16*)d_in[4], (const __nv_bfloat16*)d_in[5], (const __nv_bfloat16*)d_in[6],
                                          (const __nv_bfloat16*)d_in[7], (__nv_bfloat16*)d_out);
}
```

```cpp
#include <cuda_runtime.h>
#include <cuda.h>
#include <cuda_bf16.h>
#include <cuda_fp16.h>
#include <stdint.h>

namespace {

constexpr int N_NODES = 25000;
constexpr int N_EDGES = 800000;
constexpr int NCTA = 132;
constexpr int NPC = 190;
constexpr int NT = 640;
constexpr int NP = 512;
constexpr int CHUNK = 6060;
constexpr int R = 8;
constexpr int LMAX = 59;
constexpr int CAP = 91;
constexpr int SPITCH = 368;
constexpr int GPITCH = 24;
constexpr int OVFCAP = 112;
constexpr uint32_t TAGMOD = (1u << 22) - 1;
constexpr uint32_t EMPTY = 0xffffffffu;
constexpr int SPIN = 1 << 16;
#define MBSPIN (1 << 22)

constexpr uint32_t SB = 1024;
constexpr uint32_t A_XR = SB;
constexpr uint32_t A_ER = A_XR + R * 8192;
constexpr uint32_t A_MR = A_ER + R * 2048;
constexpr uint32_t A_QH = A_MR + 2048;
constexpr uint32_t A_TAB = A_QH + 2 * 32768;
constexpr uint32_t A_CNT = A_TAB + (LMAX + 1) * 512;
constexpr uint32_t A_KEY = A_CNT + 136 * 4;
constexpr uint32_t A_HIST = A_KEY + 224 * 4;
constexpr uint32_t A_LEN = A_HIST + 32 * 4;
constexpr uint32_t A_EV = A_LEN + 32 * 4;
constexpr uint32_t A_MISC = A_EV + (LMAX + 3) * 8;
constexpr uint32_t A_ZEND = A_MISC + 32;
constexpr uint32_t A_FIRST = A_ZEND;
constexpr uint32_t A_TAG = A_FIRST + 8;
constexpr uint32_t A_ROW = A_FIRST + 16;
constexpr uint32_t A_MT = A_ROW + 192 * 2;
constexpr uint32_t A_B1 = A_MT + 64 * 4;
constexpr uint32_t A_B2 = A_B1 + 256;
constexpr uint32_t A_INFO = A_B2 + 128;
constexpr uint32_t A_BAR = A_INFO + 196 * 4;
constexpr uint32_t A_OVF = A_BAR + 18 * 8;
constexpr uint32_t A_SS = A_OVF + OVFCAP * 8;
constexpr uint32_t A_END = A_SS + 4 * 512;
constexpr int SMEM_BYTES = A_END - SB;
constexpr uint32_t A_STG = A_XR;
constexpr uint32_t A_WB = A_QH + 192 * 128;
constexpr uint32_t A_WA = A_XR + 49 * 1024;
constexpr uint32_t A_XO = A_TAB;
constexpr uint32_t A_W2 = A_TAB;
constexpr uint32_t A_OUT = A_XR;
static_assert(A_STG + (NCTA + 1) * SPITCH + 16 <= A_WA && A_WA + 2 * 10240 <= A_QH && A_XO + 192 * 128 <= A_CNT && (LMAX + 1) % 4 == 0, "alias");
static_assert(A_QH % 1024 == 0 && A_TAB % 1024 == 0 && A_WA % 1024 == 0, "align");
static_assert(A_CNT % 16 == 0 && A_ZEND % 16 == 0 && A_B2 % 16 == 0 && A_B1 % 16 == 0 && A_BAR % 8 == 0 && A_KEY % 16 == 0 && A_EV % 8 == 0 && A_MISC % 16 == 0 && A_SS % 16 == 0, "align");
static_assert(SMEM_BYTES <= 199680, "smem");

struct Scratch {
    uint4 flag[NCTA * 40];
    uint32_t cnt, pad[31];
    uint4 x16[(N_NODES + 1) * 8];
    uint4 ent[NCTA * NCTA * GPITCH];
};
__device__ __align__(128) Scratch g_scratch;

#define TL(i)
#define TC(i)
#define TV(i, v)
#define TS(i)
#define TW(i)
#define TWD(i, v)
#define TSX(i, cond)

__device__ __forceinline__ void wg_fence() { asm volatile("wgmma.fence.sync.aligned;" ::: "memory"); }
__device__ __forceinline__ void wg_commit() { asm volatile("wgmma.commit_group.sync.aligned;" ::: "memory"); }
__device__ __forceinline__ void wg_wait0() { asm volatile("wgmma.wait_group.sync.aligned 0;" ::: "memory"); }
template <int M> __device__ __forceinline__ void fence_regs(uint32_t (&d)[M]) {
#pragma unroll
    for (int i = 0; i < M; i++) asm volatile("" : "+r"(d[i])::"memory");
}
template <int M> __device__ __forceinline__ void fence_regs(float (&d)[M]) {
#pragma unroll
    for (int i = 0; i < M; i++) asm volatile("" : "+f"(d[i])::"memory");
}
constexpr uint32_t HI128 = 0x40000040;
constexpr uint32_t HI32 = 0xC0000010;
template <int SC, uint32_t HI>
__device__ __forceinline__ void mma64h(uint32_t (&d)[16], const uint32_t (&a)[4], uint32_t lo) {
    asm volatile("{\n.reg .pred p;\n.reg .b64 dsc;\nsetp.ne.b32 p, %21, 0;\nmov.b64 dsc, {%20, %22};\n"
        "wgmma.mma_async.sync.aligned.m64n64k16.f16.f16.f16 {%0, %1, %2, %3, %4, %5, %6, %7, %8, %9, %10, %11, %12, %13, %14, %15}, {%16, %17, %18, %19}, dsc, p, 1, 1, 0;\n}\n"
        : "+r"(d[0]), "+r"(d[1]), "+r"(d[2]), "+r"(d[3]), "+r"(d[4]), "+r"(d[5]), "+r"(d[6]), "+r"(d[7]), "+r"(d[8]), "+r"(d[9]), "+r"(d[10]), "+r"(d[11]), "+r"(d[12]), "+r"(d[13]), "+r"(d[14]), "+r"(d[15])
        : "r"(a[0]), "r"(a[1]), "r"(a[2]), "r"(a[3]), "r"(lo), "n"(SC), "n"(HI));
}
template <int SC, uint32_t HI>
__device__ __forceinline__ void mma96h(uint32_t (&d)[24], const uint32_t (&a)[4], uint32_t lo) {
    asm volatile("{\n.reg .pred p;\n.reg .b64 dsc;\nsetp.ne.b32 p, %29, 0;\nmov.b64 dsc, {%28, %30};\n"
        "wgmma.mma_async.sync.aligned.m64n96k16.f16.f16.f16 {%0, %1, %2, %3, %4, %5, %6, %7, %8, %9, %10, %11, %12, %13, %14, %15, %16, %17, %18, %19, %20, %21, %22, %23}, {%24, %25, %26, %27}, dsc, p, 1, 1, 0;\n}\n"
        : "+r"(d[0]), "+r"(d[1]), "+r"(d[2]), "+r"(d[3]), "+r"(d[4]), "+r"(d[5]), "+r"(d[6]), "+r"(d[7]), "+r"(d[8]), "+r"(d[9]), "+r"(d[10]), "+r"(d[11]), "+r"(d[12]), "+r"(d[13]), "+r"(d[14]), "+r"(d[15]), "+r"(d[16]), "+r"(d[17]), "+r"(d[18]), "+r"(d[19]), "+r"(d[20]), "+r"(d[21]), "+r"(d[22]), "+r"(d[23])
        : "r"(a[0]), "r"(a[1]), "r"(a[2]), "r"(a[3]), "r"(lo), "n"(SC), "n"(HI));
}
template <int SC, uint32_t HI>
__device__ __forceinline__ void mma48f(float (&d)[24], const uint32_t (&a)[4], uint32_t lo) {
    asm volatile("{\n.reg .pred p;\n.reg .b64 dsc;\nsetp.ne.b32 p, %29, 0;\nmov.b64 dsc, {%28, %30};\n"
        "wgmma.mma_async.sync.aligned.m64n48k16.f32.f16.f16 {%0, %1, %2, %3, %4, %5, %6, %7, %8, %9, %10, %11, %12, %13, %14, %15, %16, %17, %18, %19, %20, %21, %22, %23}, {%24, %25, %26, %27}, dsc, p, 1, 1, 0;\n}\n"
        : "+f"(d[0]), "+f"(d[1]), "+f"(d[2]), "+f"(d[3]), "+f"(d[4]), "+f"(d[5]), "+f"(d[6]), "+f"(d[7]), "+f"(d[8]), "+f"(d[9]), "+f"(d[10]), "+f"(d[11]), "+f"(d[12]), "+f"(d[13]), "+f"(d[14]), "+f"(d[15]), "+f"(d[16]), "+f"(d[17]), "+f"(d[18]), "+f"(d[19]), "+f"(d[20]), "+f"(d[21]), "+f"(d[22]), "+f"(d[23])
        : "r"(a[0]), "r"(a[1]), "r"(a[2]), "r"(a[3]), "r"(lo), "n"(SC), "n"(HI));
}
__device__ __forceinline__ uint32_t hadd2(uint32_t a, uint32_t b) { uint32_t r; asm("add.rn.f16x2 %0, %1, %2;" : "=r"(r) : "r"(a), "r"(b)); return r; }
__device__ __forceinline__ uint32_t hfma2(uint32_t a, uint32_t b, uint32_t c) { uint32_t r; asm("fma.rn.f16x2 %0, %1, %2, %3;" : "=r"(r) : "r"(a), "r"(b), "r"(c)); return r; }
__device__ __forceinline__ uint32_t htanh2(uint32_t a) { uint32_t r; asm("tanh.approx.f16x2 %0, %1;" : "=r"(r) : "r"(a)); return r; }
__device__ __forceinline__ uint32_t pack_h2(float lo, float hi) { uint32_t r; asm("cvt.rn.f16x2.f32 %0, %1, %2;" : "=r"(r) : "f"(hi), "f"(lo)); return r; }
__device__ __forceinline__ uint32_t pack_b2(float lo, float hi) { uint32_t r; asm("cvt.rn.bf16x2.f32 %0, %1, %2;" : "=r"(r) : "f"(hi), "f"(lo)); return r; }
__device__ __forceinline__ uint32_t bf2h(uint32_t v) { return pack_h2(__uint_as_float(v << 16), __uint_as_float(v & 0xffff0000u)); }
__device__ __forceinline__ uint32_t bf2h_half(uint32_t v) { return pack_h2(0.5f * __uint_as_float(v << 16), 0.5f * __uint_as_float(v & 0xffff0000u)); }
__device__ __forceinline__ uint4 bf2h4(uint4 v) { return make_uint4(bf2h(v.x), bf2h(v.y), bf2h(v.z), bf2h(v.w)); }

__device__ __forceinline__ void cp16(uint32_t s, const void* g) { asm volatile("cp.async.cg.shared.global [%0], [%1], 16;" ::"r"(s), "l"(g) : "memory"); }
__device__ __forceinline__ void cp16z(uint32_t s, const void* g, bool ignore) {
    asm volatile("{\n.reg .pred p;\nsetp.ne.u32 p, %2, 0;\ncp.async.cg.shared.global [%0], [%1], 16, p;\n}" ::"r"(s), "l"(g), "r"((uint32_t)ignore) : "memory");
}
__device__ __forceinline__ void cp_commit() { asm volatile("cp.async.commit_group;" ::: "memory"); }
template <int N> __device__ __forceinline__ void cp_wait() { asm volatile("cp.async.wait_group %0;" ::"n"(N) : "memory"); }
__device__ __forceinline__ void bulk_g2s(uint32_t s, const void* g, uint32_t bytes, uint32_t bar) {
    asm volatile("cp.async.bulk.shared::cluster.global.mbarrier::complete_tx::bytes [%0], [%1], %2, [%3];" ::"r"(s), "l"(g), "r"(bytes), "r"(bar) : "memory");
}
__device__ __forceinline__ void tma_g2s(uint32_t s, const CUtensorMap* m, int c0, int c1, uint32_t bar) {
    asm volatile("cp.async.bulk.tensor.2d.shared::cluster.global.mbarrier::complete_tx::bytes [%0], [%1, {%2, %3}], [%4];" ::"r"(s), "l"(m), "r"(c0), "r"(c1), "r"(bar) : "memory");
}
__device__ __forceinline__ void l2_prefetch(const void* g, uint32_t bytes) { asm volatile("cp.async.bulk.prefetch.L2.global [%0], %1;" ::"l"(g), "r"(bytes) : "memory"); }
__device__ __forceinline__ void proxy_fence() { asm volatile("fence.proxy.async.shared::cta;" ::: "memory"); }
__device__ __forceinline__ bool mbar_try(uint32_t bar, uint32_t parity) {
    uint32_t ok;
    asm volatile("{\n.reg .pred p;\nmbarrier.try_wait.parity.shared::cta.b64 p, [%1], %2;\nselp.u32 %0, 1, 0, p;\n}" : "=r"(ok) : "r"(bar), "r"(parity) : "memory");
    return ok;
}
__device__ __forceinline__ void mbar_wait(uint32_t bar, uint32_t parity) {
    if (__builtin_expect(!mbar_try(bar, parity), 0))
        for (int it = 0; it < MBSPIN; it++) if (mbar_try(bar, parity)) break;
}
__device__ __forceinline__ void mbar_arrive(uint32_t bar) { asm volatile("mbarrier.arrive.shared::cta.b64 _, [%0];" ::"r"(bar) : "memory"); }
__device__ __forceinline__ uint32_t lds32(uint32_t a) { uint32_t r; asm volatile("ld.shared.u32 %0, [%1];" : "=r"(r) : "r"(a) : "memory"); return r; }
__device__ __forceinline__ uint32_t lds16(uint32_t a) { uint32_t r; asm volatile("ld.shared.u16 %0, [%1];" : "=r"(r) : "r"(a) : "memory"); return r; }
__device__ __forceinline__ uint32_t lds8(uint32_t a) { uint32_t r; asm volatile("ld.shared.u8 %0, [%1];" : "=r"(r) : "r"(a) : "memory"); return r; }
__device__ __forceinline__ uint2 lds64(uint32_t a) { uint2 r; asm volatile("ld.shared.v2.u32 {%0,%1}, [%2];" : "=r"(r.x), "=r"(r.y) : "r"(a) : "memory"); return r; }
__device__ __forceinline__ uint4 lds128(uint32_t a) { uint4 r; asm volatile("ld.shared.v4.u32 {%0,%1,%2,%3}, [%4];" : "=r"(r.x), "=r"(r.y), "=r"(r.z), "=r"(r.w) : "r"(a) : "memory"); return r; }
__device__ __forceinline__ void sts128(uint32_t a, uint4 v) { asm volatile("st.shared.v4.u32 [%0], {%1,%2,%3,%4};" ::"r"(a), "r"(v.x), "r"(v.y), "r"(v.z), "r"(v.w) : "memory"); }
__device__ __forceinline__ void sts64(uint32_t a, uint32_t x, uint32_t y) { asm volatile("st.shared.v2.u32 [%0], {%1,%2};" ::"r"(a), "r"(x), "r"(y) : "memory"); }
__device__ __forceinline__ void sts32(uint32_t a, uint32_t v) { asm volatile("st.shared.u32 [%0], %1;" ::"r"(a), "r"(v) : "memory"); }
__device__ __forceinline__ void sts16(uint32_t a, uint32_t v) { asm volatile("st.shared.u16 [%0], %1;" ::"r"(a), "r"(v) : "memory"); }
__device__ __forceinline__ void sts8(uint32_t a, uint32_t v) { asm volatile("st.shared.u8 [%0], %1;" ::"r"(a), "r"(v) : "memory"); }
__device__ __forceinline__ uint32_t atoms_inc(uint32_t a) { uint32_t r; asm volatile("atom.shared.add.u32 %0, [%1], 1;" : "=r"(r) : "r"(a) : "memory"); return r; }
__device__ __forceinline__ void reds_max(uint32_t a, uint32_t v) { asm volatile("red.shared.max.u32 [%0], %1;" ::"r"(a), "r"(v) : "memory"); }
__device__ __forceinline__ uint32_t ldg_rlx32(const void* p) { uint32_t r; asm volatile("ld.relaxed.gpu.global.u32 %0, [%1];" : "=r"(r) : "l"(p) : "memory"); return r; }
#define LDI "ld.relaxed.gpu.global.v2.u32"
__device__ __forceinline__ int2 ldg64(const void* p) { int2 r; asm volatile(LDI " {%0,%1}, [%2];" : "=r"(r.x), "=r"(r.y) : "l"(p) : "memory"); return r; }
__device__ __forceinline__ void ldg64_if(int2& r, const void* p, bool on) {
    asm volatile("{\n.reg .pred p;\nsetp.ne.u32 p, %3, 0;\n@p " LDI " {%0,%1}, [%2];\n}" : "+r"(r.x), "+r"(r.y) : "l"(p), "r"((uint32_t)on) : "memory");
}
__device__ __forceinline__ uint4 ldg_rlx128_if(const void* p, bool on) {
    uint4 r;
    asm volatile("{\n.reg .pred p;\n.reg .b64 a, b;\nsetp.ne.u32 p, %5, 0;\n@p ld.relaxed.gpu.global.v2.b64 {a, b}, [%4];\nmov.b64 {%0,%1}, a;\nmov.b64 {%2,%3}, b;\n}"
                 : "=r"(r.x), "=r"(r.y), "=r"(r.z), "=r"(r.w) : "l"(p), "r"((uint32_t)on) : "memory");
    return r;
}
__device__ __forceinline__ void ldg_rlx128_upd(uint64_t& a, uint64_t& b, const void* p, bool on) {
    asm volatile("{\n.reg .pred p;\nsetp.ne.u32 p, %3, 0;\n@p ld.relaxed.gpu.global.v2.b64 {%0, %1}, [%2];\n}" : "+l"(a), "+l"(b) : "l"(p), "r"((uint32_t)on) : "memory");
}
__device__ __forceinline__ uint2 ldg_rlx64_if(const void* p, bool on) {
    uint64_t a = 0;
    asm volatile("{\n.reg .pred p;\nsetp.ne.u32 p, %2, 0;\n@p ld.relaxed.gpu.global.b64 %0, [%1];\n}" : "+l"(a) : "l"(p), "r"((uint32_t)on) : "memory");
    return make_uint2((uint32_t)a, (uint32_t)(a >> 32));
}
__device__ __forceinline__ uint4 ldg_acq128(const void* p) {
    uint4 r;
    asm volatile("ld.acquire.gpu.global.v4.u32 {%0,%1,%2,%3}, [%4];" : "=r"(r.x), "=r"(r.y), "=r"(r.z), "=r"(r.w) : "l"(p) : "memory");
    return r;
}
__device__ __forceinline__ void stg_rlx32(void* p, uint32_t v) { asm volatile("st.relaxed.gpu.global.u32 [%0], %1;" ::"l"(p), "r"(v) : "memory"); }
__device__ __forceinline__ void stg_rlx128(void* p, uint4 v) {
    asm volatile("{\n.reg .b64 a, b;\nmov.b64 a, {%1,%2};\nmov.b64 b, {%3,%4};\nst.relaxed.gpu.global.v2.b64 [%0], {a, b};\n}" ::"l"(p), "r"(v.x), "r"(v.y), "r"(v.z), "r"(v.w) : "memory");
}
__device__ __forceinline__ void stg_rlx128_if(void* p, uint4 v, bool on) {
    asm volatile("{\n.reg .pred p;\n.reg .b64 a, b;\nsetp.ne.u32 p, %5, 0;\nmov.b64 a, {%1,%2};\nmov.b64 b, {%3,%4};\n@p st.relaxed.gpu.global.v2.b64 [%0], {a, b};\n}" ::"l"(p), "r"(v.x), "r"(v.y), "r"(v.z), "r"(v.w), "r"((uint32_t)on) : "memory");
}
__device__ __forceinline__ void ldsm4t(uint32_t (&r)[4], uint32_t a) {
    asm volatile("ldmatrix.sync.aligned.m8n8.x4.trans.shared.b16 {%0,%1,%2,%3}, [%4];" : "=r"(r[0]), "=r"(r[1]), "=r"(r[2]), "=r"(r[3]) : "r"(a) : "memory");
}
__device__ __forceinline__ void ldsm2t(uint32_t& r0, uint32_t& r1, uint32_t a) {
    asm volatile("ldmatrix.sync.aligned.m8n8.x2.trans.shared.b16 {%0,%1}, [%2];" : "=r"(r0), "=r"(r1) : "r"(a) : "memory");
}
__device__ __forceinline__ void stsm2t(uint32_t a, uint32_t r0, uint32_t r1) {
    asm volatile("stmatrix.sync.aligned.m8n8.x2.trans.shared.b16 [%0], {%1,%2};" ::"r"(a), "r"(r0), "r"(r1) : "memory");
}
__device__ __forceinline__ void stsm4t(uint32_t a, uint32_t r0, uint32_t r1, uint32_t r2, uint32_t r3) {
    asm volatile("stmatrix.sync.aligned.m8n8.x4.trans.shared.b16 [%0], {%1,%2,%3,%4};" ::"r"(a), "r"(r0), "r"(r1), "r"(r2), "r"(r3) : "memory");
}
template <int ID, int N> __device__ __forceinline__ void bar_sync() { asm volatile("bar.sync %0, %1;" ::"n"(ID), "n"(N) : "memory"); }
template <int ID, int N> __device__ __forceinline__ void bar_arrive() { asm volatile("bar.arrive %0, %1;" ::"n"(ID), "n"(N) : "memory"); }
__device__ __forceinline__ uint32_t scan_up(uint32_t v) {
#pragma unroll
    for (int o = 1; o < 32; o <<= 1)
        asm volatile("{\n.reg .pred p;\n.reg .u32 t;\nshfl.sync.up.b32 t|p, %0, %1, 0, -1;\n@p add.u32 %0, %0, t;\n}" : "+r"(v) : "r"(o));
    return v;
}
__device__ __forceinline__ uint32_t scan_down(uint32_t v) {
#pragma unroll
    for (int o = 1; o < 32; o <<= 1)
        asm volatile("{\n.reg .pred p;\n.reg .u32 t;\nshfl.sync.down.b32 t|p, %0, %1, 31, -1;\n@p add.u32 %0, %0, t;\n}" : "+r"(v) : "r"(o));
    return v;
}
__device__ __forceinline__ float bf2f(const __nv_bfloat16* p) { return __bfloat162float(*p); }

__device__ __forceinline__ int chunk_start(int c) { return c * CHUNK + min(c, 40) * 2; }
static_assert(NCTA * CHUNK + 80 == N_EDGES && CHUNK / 2 + 1 <= 6 * NP && CHUNK / 2 >= 5 * NP, "chunks");

__device__ __noinline__ void slow_path(uint8_t* sp, const __nv_bfloat16* x, const __nv_bfloat16* ea, const int* src, const int* dst,
                                       const __nv_bfloat16* w1, const __nv_bfloat16* b1, const __nv_bfloat16* w2,
                                       const __nv_bfloat16* b2, __nv_bfloat16* out) {
    const int tid = threadIdx.x, lane = tid & 31, warp = tid >> 5, cta = blockIdx.x;
    const int nrows = min(NPC, N_NODES - cta * NPC);
    float* hs = (float*)sp;
    __nv_bfloat16* w1s = (__nv_bfloat16*)(sp + 192 * 128 * 4);
    int* dg = (int*)(sp + 192 * 128 * 4 + 144 * 128 * 2);
    __syncthreads();
    for (int i = tid; i < 192 * 128; i += NT) hs[i] = 0.f;
    for (int i = tid; i < 144 * 128; i += NT) w1s[i] = w1[i];
    for (int i = tid; i < 192; i += NT) dg[i] = 0;
    __syncthreads();
    float bb[4];
    for (int j = 0; j < 4; j++) bb[j] = bf2f(b1 + lane * 4 + j);
    for (int i0 = warp * 32; i0 < N_EDGES; i0 += NT) {
        const int mine = dst[i0 + lane] - cta * NPC;
        uint32_t hit = __ballot_sync(0xffffffffu, (unsigned)mine < (unsigned)nrows);
        while (hit) {
            const int b = __ffs(hit) - 1;
            hit &= hit - 1;
            const int eid = i0 + b, dl = __shfl_sync(0xffffffffu, mine, b), s = src[eid];
            float v[5];
            v[0] = bf2f(x + s * 64 + lane); v[1] = bf2f(x + s * 64 + 32 + lane);
            v[2] = bf2f(x + (cta * NPC + dl) * 64 + lane); v[3] = bf2f(x + (cta * NPC + dl) * 64 + 32 + lane);
            v[4] = lane < 16 ? bf2f(ea + (size_t)eid * 16 + lane) : 0.f;
            float z[4] = {bb[0], bb[1], bb[2], bb[3]};
#pragma unroll
            for (int c = 0; c < 5; c++) {
                for (int kk = 0; kk < (c == 4 ? 16 : 32); kk++) {
                    float a = __shfl_sync(0xffffffffu, v[c], kk);
                    const __nv_bfloat16* wr = w1s + (c * 32 + kk) * 128 + lane * 4;
#pragma unroll
                    for (int j = 0; j < 4; j++) z[j] = fmaf(a, __bfloat162float(wr[j]), z[j]);
                }
            }
#pragma unroll
            for (int j = 0; j < 4; j++) atomicAdd(&hs[dl * 128 + lane * 4 + j], z[j] / (1.f + expf(-z[j])));
            if (lane == 0) atomicAdd(&dg[dl], 1);
        }
    }
    __syncthreads();
    for (int i = tid; i < nrows * 64; i += NT) {
        int n = i >> 6, d = i & 63;
        float a = 0.f;
        if (dg[n] > 0) {
            a = (float)dg[n] * bf2f(b2 + d);
            for (int h = 0; h < 128; h++) a = fmaf(hs[n * 128 + h], bf2f(w2 + h * 64 + d), a);
        }
        out[(size_t)(cta * NPC + n) * 64 + d] = __float2bfloat16(a);
    }
}

__global__ void __launch_bounds__(NT, 1)
mpnn_kernel(const __nv_bfloat16* __restrict__ x, const __nv_bfloat16* __restrict__ ea, const int* __restrict__ src,
            const int* __restrict__ dst, const __nv_bfloat16* __restrict__ w1, const __nv_bfloat16* __restrict__ b1,
            const __nv_bfloat16* __restrict__ w2, const __nv_bfloat16* __restrict__ b2, __nv_bfloat16* __restrict__ out,
            Scratch* __restrict__ gs, const __grid_constant__ CUtensorMap w1map) {
    extern __shared__ uint8_t smem_raw[];
    const int tid = threadIdx.x, lane = tid & 31;
    __builtin_assume(tid < NT);
    const int warp = __shfl_sync(0xffffffffu, tid >> 5, 0);
    const int cta = blockIdx.x;
    const int nrows = min(NPC, N_NODES - cta * NPC);
    const int e0 = chunk_start(cta);
    const int nv2 = CHUNK / 2 + (cta < 40);
    if ((uint32_t)__cvta_generic_to_shared(smem_raw) != SB || !gs) { slow_path(smem_raw, x, ea, src, dst, w1, b1, w2, b2, out); return; }
    constexpr uint32_t bar_w = A_BAR + R * 16, bar_x = bar_w + 8;
    const int wg = warp >> 2, wq = warp & 3, hh = wg & 1, strm = wg >> 1;
    const uint32_t qch = wq * 2 + ((lane >> 3) & 1);
    const uint32_t wofs = (((lane >> 4) & 1) * 8 + (lane & 7)) * 128 + ((qch ^ (lane & 7)) << 4);
    int bad = 0;
    TS(0);

    int2 d2[6];
    const int pt = tid - NP;
    if (wg == 4) {
        uint32_t cnt0;
        if (pt == 64) cnt0 = ldg_rlx32(&gs->cnt);
        if (pt == 96) {
#pragma unroll
            for (int i = 0; i < 2 * R + 2; i++) asm volatile("mbarrier.init.shared::cta.b64 [%0], %1;" ::"r"(A_BAR + i * 8), "r"(i < R ? 2 : i < 2 * R ? 8 : 1) : "memory");
            proxy_fence();
            asm volatile("mbarrier.arrive.expect_tx.shared::cta.b64 _, [%0], %1;" ::"r"(bar_w), "r"(144 * 256 + 256 + 128) : "memory");
            asm volatile("mbarrier.arrive.expect_tx.shared::cta.b64 _, [%0], %1;" ::"r"(bar_x), "r"(nrows * 128) : "memory");
        }
        __syncwarp();
        {
            const uint32_t k = pt - (A_KEY - A_CNT) / 16, o = k < 56 ? 1u << 18 : 0u;
            sts128(A_CNT + pt * 16, make_uint4(4 * k * o, (4 * k + 1) * o, (4 * k + 2) * o, (4 * k + 3) * o));
            if (pt < (int)(A_ZEND - A_CNT) / 16 - 128) sts128(A_CNT + 2048 + pt * 16, make_uint4(0, 0, 0, 0));
        }
        if (pt < 64) sts32(A_MT + pt * 4, 0xffffffffu / ((pt + 1) * 512) + 1);
        if (pt == 64) {
            const uint32_t tag = cnt0 / NCTA + 1;
            sts128(A_FIRST, make_uint4(0x60606060u, 0x60606060u, tag << 21, tag >> 11 << 21));
        }
    } else {
        const int2* dp = (const int2*)(dst + e0) + tid;
        d2[5] = make_int2(NCTA * NPC, NCTA * NPC);
#pragma unroll
        for (int r = 0; r < 5; r++) d2[r] = ldg64(dp + r * NP);
        ldg64_if(d2[5], dp + 5 * NP, tid < nv2 - 5 * NP);
        stg_rlx128_if(gs->ent + ((tid >> 1) * NCTA + cta) * GPITCH + (lane & 1), make_uint4(0, 0, 0, 0), tid < 2 * NCTA);
    }
    __syncthreads();
    const uint2 tag = lds64(A_TAG);
    if (wg == 4) {
        const uint32_t tagw = tag.x | tag.y >> 11;
        if (warp == 19) {
            if (lane == 0) {
                bulk_g2s(A_XO, x + cta * NPC * 64, nrows * 128, bar_x);
                asm volatile("red.relaxed.gpu.global.inc.u32 [%0], %1;" ::"l"(&gs->cnt), "r"(NCTA * TAGMOD - 1) : "memory");
            }
            TSX(15, lane == 0);
            __syncwarp();
            if (lane < 18) {
                int i = lane + cta % 18;
                i = i >= 18 ? i - 18 : i;
                const int h = i & 1, rb = i >> 1;
                tma_g2s(rb >= 4 && rb < 8 ? A_WB + h * 32768 + (rb - 4) * 2048 : A_WA + h * 10240 + min(rb, 4) * 2048, &w1map, h * 64, rb * 16, bar_w);
            } else if (lane < 20) bulk_g2s(lane == 18 ? A_B1 : A_B2, lane == 18 ? b1 : b2, lane == 18 ? 256 : 128, bar_w);
            else if (lane == 20) l2_prefetch(w2, 128 * 64 * 2);
            else if (lane == 21) gs->flag[cta * 40 + 36].x = N_NODES;
            __syncwarp();
        }
        mbar_wait(bar_x, 0);
        TW(0);
        const uint32_t xo = A_XO + (pt >> 3) * 128 + (((pt ^ (pt >> 3)) & 7) << 4);
        {
            uint4 xr[12];
#pragma unroll
            for (int r = 0; r < 12; r++) xr[r] = lds128(A_XO + (r * 128 + pt) * 16);
            __syncwarp();
#pragma unroll
            for (int r = 0; r < 12; r++) {
                const bool in = r * 128 + pt < nrows * 8;
                const uint4 v = in ? bf2h4(xr[r]) : make_uint4(0, 0, 0, 0);
                sts128(xo + r * 2048, v);
                if (in) gs->x16[cta * NPC * 8 + r * 128 + pt] = v;
            }
        }
        proxy_fence();
        mbar_wait(bar_w, 0);
        bar_sync<4, 128>();
        TW(1);
        if (warp == 19) {
            asm volatile("fence.acq_rel.gpu;" ::: "memory");
#pragma unroll
            for (int j = 0; j < 5; j++)
                if (j * 32 + lane < NCTA) stg_rlx32((uint32_t*)(gs->flag + (j * 32 + lane) * 40) + cta, tagw);
            TSX(16, lane == 0);
            __syncwarp();
        }
#pragma unroll 1
        for (int h = 0; h < 2; h++) {
            uint32_t wb[4][4], acc[2][24];
#pragma unroll
            for (int i = 0; i < 4; i++) ldsm4t(wb[i], A_WB + h * 32768 + wofs + i * 2048);
            const uint32_t bl0 = lds16(A_B1 + (h * 64 + wq * 16 + (lane >> 2)) * 2), bl1 = lds16(A_B1 + (h * 64 + wq * 16 + 8 + (lane >> 2)) * 2);
#pragma unroll
            for (int i = 0; i < 4; i++)
#pragma unroll
                for (int j = 0; j < 4; j++) wb[i][j] = bf2h_half(wb[i][j]);
            const uint32_t bq0 = bf2h_half(bl0 * 0x10001u), bq1 = bf2h_half(bl1 * 0x10001u);
#pragma unroll
            for (int i = 0; i < 4; i++) fence_regs(wb[i]);
            wg_fence();
#pragma unroll
            for (int n = 0; n < 2; n++) {
                const uint32_t lo = ((A_XO >> 4) | 0x10000) + n * 768;
                mma96h<0, HI128>(acc[n], wb[0], lo);
                mma96h<1, HI128>(acc[n], wb[1], lo + 2);
                mma96h<1, HI128>(acc[n], wb[2], lo + 4);
                mma96h<1, HI128>(acc[n], wb[3], lo + 6);
            }
            wg_commit();
            wg_wait0();
            fence_regs(acc[0]); fence_regs(acc[1]);
#pragma unroll
            for (int n = 0; n < 2; n++)
#pragma unroll
                for (int j = 0; j < 6; j++)
                    stsm4t(A_QH + h * 32768 + n * 12288 + wofs + j * 2048, hadd2(acc[n][4 * j], bq0), hadd2(acc[n][4 * j + 1], bq1), hadd2(acc[n][4 * j + 2], bq0), hadd2(acc[n][4 * j + 3], bq1));
        }
        if (pt == 64) l2_prefetch(src + cta * 6064, min(6064, N_EDGES - cta * 6064) * 4);
        bar_sync<4, 128>();
#pragma unroll 5
        for (int r = 0; r < (LMAX + 1) / 4; r++) sts128(A_TAB + (r * 128 + pt) * 16, make_uint4(EMPTY, EMPTY, EMPTY, EMPTY));
        bar_arrive<12, NT>();
        TW(2);
        if (warp == 19) {
            bool ok = false;
            for (int it = 0; it < SPIN && !ok; it++) {
                const uint4 f0 = ldg_acq128(gs->flag + cta * 40 + lane), f1 = ldg_acq128(gs->flag + cta * 40 + 32);
                ok = __all_sync(0xffffffffu, f0.x == tagw && f0.y == tagw && f0.z == tagw && f0.w == tagw && f1.x == tagw && f1.y == tagw && f1.z == tagw && f1.w == tagw);
            }
            bad = !ok;
            TSX(17, lane == 0);
        }
        const int par = wq >> 1, hf = wq & 1, gq = lane >> 3, cp = (lane >> 1) & 3;
        const uint32_t bar_full = A_BAR + hf * 8, bar_empty = bar_full + R * 8;
        uint32_t xd[8];
#pragma unroll
        for (int c = 0; c < 8; c++) xd[c] = A_XR + hf * 8192 + (par * 32 + gq * 8) * 128 + (((lane & 7) ^ c) << 4);
        fence_regs(xd);
        uint32_t ed0 = A_ER + hf * 2048 + (par * 32 + gq * 8 + cp) * 32 + (lane & 1) * 16, ed1 = (ed0 ^ 16) + 128;
        uint32_t md = A_MR + hf * 128 + (cp >> 1) * 32 + (par * 4 + gq) * 4 + (cp & 1) * 2;
        uint32_t tl = A_TAB + par * 256 + hf * 128 + lane * 4, te = A_TAB + par * 256 + hf * 128 + gq * 32 + cp * 4;
        const uint32_t sw = A_SS + wq * 128 + lane * 4, sr = A_SS + wq * 128 + gq * 32;
        const int* nn = (const int*)(gs->flag + cta * 40 + 36);
        const char* xg = (const char*)gs->x16 + (lane & 7) * 16;
        const char* eg = (const char*)ea + (lane & 1) * 16;
        const int* sp = src;
        asm volatile("" : "+l"(xg), "+l"(eg), "+l"(nn), "+l"(sp), "+r"(ed0), "+r"(ed1), "+r"(md));
        auto finish = [&](int u) {
            const uint4 v0 = lds128(ed0 + u * 4096), v1 = lds128(ed1 + u * 4096);
            sts128(ed0 + u * 4096, bf2h4(v0));
            sts128(ed1 + u * 4096, bf2h4(v1));
            proxy_fence();
            __syncwarp();
            if (lane == 0) mbar_arrive(bar_full + u * 16);
        };
        auto issue_e = [&](int st, uint32_t e0, uint32_t e1) {
            cp16z(ed0 + st * 4096, eg + (size_t)e0 * 32, e0 == EMPTY);
            cp16z(ed1 + st * 4096, eg + (size_t)e1 * 32, e1 == EMPTY);
            sts16(md + st * 256, e0 == EMPTY ? 0 : 0x3c00);
            sts16(md + st * 256 + 64, e1 == EMPTY ? 0 : 0x3c00);
        };
        auto issue_x = [&](int st, const uint4& a0, const uint4& a1) {
            const uint32_t a[8] = {a0.x, a0.y, a0.z, a0.w, a1.x, a1.y, a1.z, a1.w};
#pragma unroll
            for (int i = 0; i < 8; i++) cp16(xd[i] + st * 16384 + i * 128, xg + (size_t)a[i] * 128);
        };
        bar_sync<5, NT>();
        TSX(9, tid == 512);
        if (lds32(A_MISC + 4)) { slow_path(smem_raw, x, ea, src, dst, w1, b1, w2, b2, out); return; }
        const int L = lds32(A_MISC + 16);
        auto fetch_src = [&](int slot, uint32_t e, bool on) {
            const int* p = nn;
            asm volatile("{\n.reg .pred p;\nsetp.ne.u32 p, %2, -1;\nsetp.ne.and.u32 p, %3, 0, p;\n@p mad.wide.u32 %0, %2, 4, %1;\n}" : "+l"(p) : "l"(sp), "r"(e), "r"((uint32_t)on));
            asm volatile("cp.async.ca.shared.global [%0], [%1], 4;" ::"r"(sw + slot * 512), "l"(p) : "memory");
        };
        {
            uint32_t es[6], ee[6];
#pragma unroll
            for (int t = 0; t < 6; t++) es[t] = lds32(tl + t * 512);
#pragma unroll
            for (int t = 0; t < 6; t++) ee[t] = lds32(te + (t >> 1) * 512 + (t & 1) * 16);
            fetch_src(0, es[0], true);
            cp_commit();
            issue_e(0, ee[0], ee[1]);
            cp_commit();
            fetch_src(1, es[1], L > 1);
            fetch_src(2, es[2], L > 2);
            cp_commit();
            cp_wait<2>();
            __syncwarp();
            issue_x(0, lds128(sr), lds128(sr + 16));
            fetch_src(3, es[3], L > 3);
            cp_commit();
            TW(4);
            cp_wait<1>();
            __syncwarp();
#pragma unroll
            for (int t = 1; t < 3; t++) {
                if (t < L) {
                    const uint4 a0 = lds128(sr + t * 512), a1 = lds128(sr + t * 512 + 16);
                    issue_e(t, ee[2 * t], ee[2 * t + 1]);
                    issue_x(t, a0, a1);
                    fetch_src(t - 1, es[t + 3], L > t + 3);
                }
                cp_commit();
            }
        }
        cp_wait<2>();
        TW(5);
        finish(0);
        TW(6);
        uint32_t ph = 1;
        for (int j = L;; j -= 4) {
#pragma unroll
            for (int u = 1; u < 5; u++) {
                if (j == u) goto done;
                if (u == 2) ph ^= 1;
                if (j > u + 2) {
                    const int st = (u + 2) & 3, off = (u + 2) * 512;
                    const uint32_t es = lds32(tl + off + 1536);
                    const uint4 a0 = lds128(sr + st * 512), a1 = lds128(sr + st * 512 + 16);
                    const uint32_t e0 = lds32(te + off), e1 = lds32(te + off + 16);
                    fetch_src((st + 3) & 3, es, j > u + 5);
                    mbar_wait(bar_empty + st * 16, ph);
                    issue_e(st, e0, e1);
                    issue_x(st, a0, a1);
                }
                cp_commit();
                cp_wait<2>();
                finish(u & 3);
            }
            tl += 2048; te += 2048;
        }
    done:
        mbar_wait(bar_empty + (L & 3) * 16, ((L >> 2) & 1) ^ 1);
        if (lane == 0) mbar_arrive(bar_full + (L & 3) * 16);
        TSX(18, tid == 512);
        uint4 v[8];
#pragma unroll
        for (int i = 0; i < 8; i++) v[i] = __ldg((const uint4*)w2 + i * 128 + pt);
        bar_sync<4, 128>();
#pragma unroll
        for (int i = 0; i < 8; i++) sts128(A_W2 + (i * 16 + (pt >> 3)) * 144 + (pt & 7) * 16, bf2h4(v[i]));
        bar_sync<3, NT>();
    } else {
        TS(1);
        const uint32_t ja = tag.x + 192 + lane, jb = tag.y + 192 + lane;
        const int nr = warp < NCTA / 2 - 64 ? 5 : 4, half = lane >> 4;
        {
            uint32_t c[12], rk[12];
#pragma unroll
            for (int i = 0; i < 12; i++) {
                c[i] = __umulhi(i & 1 ? d2[i >> 1].y : d2[i >> 1].x, 44151u << 9);
                rk[i] = atoms_inc(A_CNT + c[i] * 4);
            }
            TS(2);
            const uint32_t tb = tag.y + (tid << 9), td = tag.x - tag.y;
#pragma unroll
            for (int i = 0; i < 12; i++)
                sts32(A_STG + 4 + c[i] * SPITCH + min(rk[i], (uint32_t)CAP) * 4,
                      (i & 1 ? d2[i >> 1].y : d2[i >> 1].x) + tb + (((i >> 1) * NP * 2 + (i & 1)) << 8) - c[i] * NPC + (rk[i] & 1) * td);
        }
        bar_sync<1, NP>();
        TS(3);
        {
            const uint32_t row = warp * 2 + half, p0 = (lane & 15) * 4;
            uint4* gp = gs->ent + (row * NCTA + cta) * GPITCH + (lane & 15);
            const uint32_t sp = A_STG + row * SPITCH + (lane & 15) * 16;
            uint32_t n[5];
            uint4 v[5];
#pragma unroll
            for (int k = 0; k < 5; k++) {
                n[k] = lds32(A_CNT + min(row + k * 32, NCTA + 1) * 4);
                v[k] = lds128(sp + k * 32 * SPITCH);
            }
            uint32_t big = 0;
#pragma unroll
            for (int k = 0; k < 5; k++) {
                if (p0 - 1 >= n[k]) v[k].x = p0 ? ja : ja + (n[k] << 8);
                if (p0 + 1 > n[k]) v[k].y = jb;
                if (p0 + 2 > n[k]) v[k].z = ja;
                if (p0 + 3 > n[k]) v[k].w = jb;
                stg_rlx128_if(gp + k * 32 * NCTA * GPITCH, v[k], (p0 & ~7u) <= n[k] && (k < 4 || nr == 5));
                if (n[k] >= 64 && (k < 4 || nr == 5)) big |= 1u << k;
            }
            while (__builtin_expect(big != 0, 0)) {
                const int k = __ffs(big) - 1;
                big &= big - 1;
                const uint32_t m = lds32(A_CNT + (row + k * 32) * 4), p = p0 + 64;
                if (p0 < 32 && (p & ~7u) <= m) {
                    uint4 u = lds128(sp + k * 32 * SPITCH + 256);
                    if (p > m) u.x = ja;
                    if (p + 1 > m) u.y = jb;
                    if (p + 2 > m) u.z = ja;
                    if (p + 3 > m) u.w = jb;
                    stg_rlx128(gp + k * 32 * NCTA * GPITCH + 16, u);
                }
            }
            __syncwarp();
        }
        TS(4); TW(0);
        uint32_t w[5][4];
        auto load_w = [&]() {
            mbar_wait(bar_w, 0);
#pragma unroll
            for (int i = 0; i < 5; i++) ldsm4t(w[i], A_WA + hh * 10240 + wofs + i * 2048);
#pragma unroll
            for (int i = 0; i < 5; i++) {
#pragma unroll
                for (int j = 0; j < 4; j++) w[i][j] = bf2h_half(w[i][j]);
                fence_regs(w[i]);
            }
        };
        TS(5);
        const uint4* rp = gs->ent + (cta * NCTA + warp * 2) * GPITCH;
        const uint4* hp = rp + (min(lane >> 1, 4) * 32 + (lane & 1)) * GPITCH;
        rp += half * GPITCH + (lane & 15);
        uint64_t en[10];
        uint32_t rk[20];
#pragma unroll
        for (int i = 0; i < 10; i++) en[i] = ja | (uint64_t)jb << 32;
        int nl = -1;
        bool fail = false;
        uint32_t pend = (1u << 2 * nr) - 1, todo = (1u << nr) - 1, got = 0;
        for (int it = 0;; it++) {
            const uint2 h = ldg_rlx64_if(hp, (pend >> lane) & 1);
            uint32_t next = 0;
#pragma unroll
            for (int k = 0; k < 5; k++) {
                if (got & (1u << k)) {
                    const uint32_t a = en[2 * k], b = en[2 * k] >> 32, c = en[2 * k + 1], d = en[2 * k + 1] >> 32;
                    if (__builtin_expect(__any_sync(0xffffffffu, ((a ^ tag.x) | (b ^ tag.y) | (c ^ tag.x) | (d ^ tag.y)) >= (1u << 21)), 0)) next |= 1u << k;
                    else {
                        rk[4 * k] = atoms_inc(A_KEY + (a & 255) * 4);
                        rk[4 * k + 1] = atoms_inc(A_KEY + (b & 255) * 4);
                        rk[4 * k + 2] = atoms_inc(A_KEY + (c & 255) * 4);
                        rk[4 * k + 3] = atoms_inc(A_KEY + (d & 255) * 4);
                    }
                }
            }
            const bool ok = ((h.x ^ tag.x) | (h.y ^ tag.y)) < (1u << 21) && ((pend >> lane) & 1);
            if (ok) nl = (h.x >> 8) & 0x1fff;
            if (ok && nl > CAP) { fail = true; nl = -1; }
            pend &= ~__ballot_sync(0xffffffffu, ok);
            uint32_t seen = 0;
#pragma unroll
            for (int k = 0; k < 5; k++) if (!(pend & (3u << 2 * k))) seen |= 1u << k;
            seen &= todo;
            todo &= ~seen;
            got = next | seen;
            if (!(got | todo)) break;
            if (it >= SPIN) { fail = true; nl = -1; break; }
            if (got) {
#pragma unroll
                for (int k = 0; k < 5; k++) ldg_rlx128_upd(en[2 * k], en[2 * k + 1], rp + k * 32 * GPITCH, (got & (1u << k)) && (lane & 15) * 4 <= __shfl_sync(0xffffffffu, nl, 2 * k + half));
            }
        }
        TW(2);
        uint32_t big = __ballot_sync(0xffffffffu, nl >= 64);
        while (__builtin_expect(big != 0, 0)) {
            const int k = __ffs(big) - 1;
            big &= big - 1;
            const int n = __shfl_sync(0xffffffffu, nl, k), row = (k >> 1) * 32 + warp * 2 + (k & 1);
            if (64 + 4 * lane <= n) {
                uint4 ex;
                bool bad = true;
                for (int it = 0; it < SPIN; it++) {
                    ex = ldg_rlx128_if(gs->ent + (cta * NCTA + row) * GPITCH + 16 + lane, true);
                    bad = ((ex.x ^ tag.x) | (ex.y ^ tag.y) | (ex.z ^ tag.x) | (ex.w ^ tag.y)) >= (1u << 21);
                    if (!bad) break;
                }
                if (bad) fail = true;
                else {
#pragma unroll
                    for (int j = 0; j < 4; j++) {
                        const uint32_t a = j == 0 ? ex.x : j == 1 ? ex.y : j == 2 ? ex.z : ex.w;
                        if (64 + 4 * lane + j <= n) {
                            const uint32_t r = atoms_inc(A_KEY + (a & 255) * 4), o = atoms_inc(A_MISC);
                            if (o < OVFCAP) sts64(A_OVF + o * 8, ((a >> 8) & 0x1fff) + chunk_start(row), r);
                        }
                    }
                }
            }
            __syncwarp();
        }
        TW(3);
        if (fail) sts32(A_MISC + 4, 1);
        bar_sync<1, NP>();
        TS(7);
        if (warp >= 10) {
            const int nd = tid - 320;
            const uint32_t deg = lds16(A_KEY + nd * 4), len = (deg + 1) >> 1, bin = min(len, 31u);
            const uint32_t r = atoms_inc(A_HIST + bin * 4);
            bar_sync<2, 192>();
            const uint32_t h = lds32(A_HIST + lane * 4);
            const uint32_t pos = __shfl_sync(0xffffffffu, scan_down(h) - h, bin) + r;
            reds_max(A_LEN + (pos >> 3) * 4, len);
            sts16(A_ROW + pos * 2, nd * 128 + ((nd & 7) << 4));
            bar_sync<2, 192>();
            const uint32_t l = lds32(A_LEN + lane * 4), inc = scan_up(l), start = inc - l;
            sts32(A_INFO + nd * 4, __shfl_sync(0xffffffffu, start, pos >> 3) * 512 + (pos & 7) * 4 - (nd << 26));
            if (warp == 15) {
                const uint32_t L = max((__shfl_sync(0xffffffffu, inc, 31) + 7) >> 3, 1u);
                if (L > LMAX || lds32(A_MISC) > OVFCAP) sts32(A_MISC + 4, 1);
                else {
                    const uint32_t M = lds32(A_MT + L * 4 - 4);
                    if (lane == 0) { sts64(A_MISC + 8, M, L * 512 - 32); sts32(A_MISC + 16, L); sts32(A_INFO + 192 * 4, L * 1024 - 32); sts64(A_EV + L * 8, ~0u, ~0u); }
                    if (l) {
                        uint32_t g = __umulhi(start * 512, M);
                        const uint32_t t = start - g * L;
                        if (t) { sts8(A_EV + t * 8 + g, lane + 1); g++; }
                        for (; g * L < inc; g++) sts8(A_FIRST + g, g * L > start ? lane | 32 : lane);
                    }
                }
            }
        }
        load_w();
        bar_sync<12, NT>();
        TS(8);
        const uint4 ms = lds128(A_MISC);
        if (!ms.y) {
#pragma unroll
            for (int i = 0; i < 20; i++)
                if (i < 16 || nr == 5) {
                    const uint32_t r = min(rk[i], 192u << 18);
                    rk[i] = lds32(A_INFO + (r >> 16)) + r * 256;
                }
#pragma unroll
            for (int i = 0; i < 20; i++)
                if (i < 16 || nr == 5) {
                    const uint32_t e = en[i >> 1] >> (i & 1) * 32, cs = chunk_start((i >> 2) * 32 + warp * 2 + half) - ((i & 1 ? tag.y : tag.x) >> 8);
                    sts32(A_TAB + rk[i] - __umulhi(rk[i], ms.z) * ms.w, (e >> 8) + cs);
                }
            if ((uint32_t)tid < ms.x) {
                const uint2 t = lds64(A_OVF + tid * 8);
                const uint32_t a = lds32(A_INFO + (t.y >> 16)) + t.y * 256;
                sts32(A_TAB + a - __umulhi(a, ms.z) * ms.w, t.x);
            }
        }
        TW(6);
        bar_arrive<5, NT>();
        if (ms.y) { slow_path(smem_raw, x, ea, src, dst, w1, b1, w2, b2, out); return; }
        const uint32_t qb = A_QH + hh * 32768, qx = qch << 4, rowa = A_ROW + (lane & 7) * 2;
        const uint32_t spare = qb + (192 + (lane & 7)) * 128 + ((qch ^ (lane & 7)) << 4);
        uint32_t acc[16], s[8], q[8], fa[4];
        {
            const uint32_t f = lds32(A_FIRST + strm * 4);
#pragma unroll
            for (int g = 0; g < 4; g++) {
                const uint32_t b = f >> (8 * g), a = qb + (lds16(rowa + (b & 31) * 16) ^ qx);
                ldsm2t(q[2 * g], q[2 * g + 1], a);
                fa[g] = (b & 32) ? spare + (strm * 4 + g) * 1024 : a;
            }
        }
        TS(10);
#pragma unroll
        for (int i = 0; i < 8; i++) s[i] = 0;
#pragma unroll
        for (int i = 0; i < 5; i++) fence_regs(w[i]);
        const uint32_t madr = A_MR + strm * 128 + (lane & 3) * 32;
        uint32_t eva = A_EV + strm * 4;
        const uint32_t lox = ((A_XR >> 4) | 0x10000) + strm * 512, loe = ((A_ER >> 4) | 0x10000) + strm * 128;
        const uint32_t bar_full = A_BAR + strm * 8, bar_empty = bar_full + R * 8;
        auto gemm = [&](int st, uint32_t ph) {
            mbar_wait(bar_full + st * 16, ph);
            wg_fence();
            mma64h<0, HI128>(acc, w[0], lox + st * 1024);
            mma64h<1, HI128>(acc, w[1], lox + st * 1024 + 2);
            mma64h<1, HI128>(acc, w[2], lox + st * 1024 + 4);
            mma64h<1, HI128>(acc, w[3], lox + st * 1024 + 6);
            mma64h<1, HI32>(acc, w[4], loe + st * 256);
            wg_commit();
        };
        uint32_t ph = 0;
        gemm(0, 0);
        TS(11); TC(21);
        for (;;) {
            TL((eva - A_EV) >> 5);
#pragma unroll
            for (int st = 0; st < 4; st++) {
                const uint32_t ev = lds32(eva + st * 8);
                const uint4 m0 = lds128(madr + st * 256), m1 = lds128(madr + st * 256 + 16);
                if (__builtin_expect(ev != 0, 0)) {
                    if (ev == ~0u) goto finished;
#pragma unroll
                    for (int g = 0; g < 4; g++) {
                        const uint32_t b = (ev >> (8 * g)) & 255;
                        if (b) {
                            const uint32_t r = lds16(rowa - 16 + b * 16);
                            stsm2t(fa[g], s[2 * g], s[2 * g + 1]);
                            fa[g] = qb + (r ^ qx);
                            ldsm2t(q[2 * g], q[2 * g + 1], fa[g]);
                            s[2 * g] = 0; s[2 * g + 1] = 0;
                        }
                    }
                }
                wg_wait0();
                fence_regs(acc);
                const uint32_t m[8] = {m0.x, m0.y, m0.z, m0.w, m1.x, m1.y, m1.z, m1.w};
                uint32_t u[16];
#pragma unroll
                for (int i = 0; i < 16; i++) u[i] = hfma2(q[((i >> 1) & 3) * 2 + (i & 1)], m[i >> 1], acc[i]);
                fence_regs(u);
                if (lane == 0) mbar_arrive(bar_empty + st * 16);
                if (st == 3) ph ^= 1;
                gemm((st + 1) & 3, ph);
#pragma unroll
                for (int i = 0; i < 16; i++) {
                    const int si = ((i >> 1) & 3) * 2 + (i & 1);
                    s[si] = hadd2(s[si], hfma2(u[i], htanh2(u[i]), u[i]));
                }
            }
            eva += 32;
        }
    finished:
        wg_wait0();
        fence_regs(acc);
        TS(12); TC(22);
#pragma unroll
        for (int g = 0; g < 4; g++)
            if (fa[g] >= qb + 192 * 128) stsm2t(fa[g], s[2 * g], s[2 * g + 1]);
        bar_sync<3, NT>();
#pragma unroll
        for (int g = 0; g < 4; g++) {
            if (fa[g] < qb + 192 * 128) {
                const uint32_t b = lds8(A_FIRST + min(strm * 4 + g + 1, 7));
                for (int g2 = strm * 4 + g + 1; g2 < 8; g2++) {
                    if ((b & 0x60) != 0x20 || lds8(A_FIRST + g2) != b) break;
                    uint32_t a0, a1;
                    ldsm2t(a0, a1, spare + g2 * 1024);
                    s[2 * g] = hadd2(s[2 * g], a0); s[2 * g + 1] = hadd2(s[2 * g + 1], a1);
                }
                stsm2t(fa[g], s[2 * g], s[2 * g + 1]);
            }
        }
        proxy_fence();
        uint32_t a2[8][4];
        const uint32_t wa = A_W2 + (((lane >> 4) & 1) * 8 + (lane & 7)) * 144 + qch * 16;
#pragma unroll
        for (int i = 0; i < 8; i++) ldsm4t(a2[i], wa + i * 16 * 144);
        const float bo0 = __uint_as_float(lds16(A_B2 + (wq * 16 + (lane >> 2)) * 2) << 16);
        const float bo1 = __uint_as_float(lds16(A_B2 + (wq * 16 + 8 + (lane >> 2)) * 2) << 16);
        float d[24];
#pragma unroll
        for (int i = 0; i < 8; i++) fence_regs(a2[i]);
        bar_sync<6, 512>();
        TS(13);
        const uint32_t lo = ((A_QH >> 4) | 0x10000) + wg * 384;
        wg_fence();
        mma48f<0, HI128>(d, a2[0], lo);
#pragma unroll
        for (int i = 1; i < 8; i++) mma48f<1, HI128>(d, a2[i], lo + (i >> 2) * 2048 + (i & 3) * 2);
        wg_commit();
        float dg[12];
#pragma unroll
        for (int j = 0; j < 6; j++) {
            const uint2 v = lds64(A_KEY + (wg * 48 + j * 8 + (lane & 3) * 2) * 4);
            dg[2 * j] = (float)(v.x & 0xffff); dg[2 * j + 1] = (float)(v.y & 0xffff);
        }
        wg_wait0();
        fence_regs(d);
        uint32_t r[12];
#pragma unroll
        for (int j = 0; j < 6; j++) {
            const float g0 = dg[2 * j], g1 = dg[2 * j + 1];
            const float v0 = g0 > 0.f ? fmaf(g0, bo0, d[4 * j]) : 0.f, v1 = g1 > 0.f ? fmaf(g1, bo0, d[4 * j + 1]) : 0.f;
            const float v2 = g0 > 0.f ? fmaf(g0, bo1, d[4 * j + 2]) : 0.f, v3 = g1 > 0.f ? fmaf(g1, bo1, d[4 * j + 3]) : 0.f;
            bad |= !(fabsf(v0) + fabsf(v1) + fabsf(v2) + fabsf(v3) < 3.0e38f);
            r[2 * j] = pack_b2(v0, v1); r[2 * j + 1] = pack_b2(v2, v3);
        }
        const uint32_t oa = A_OUT + (wg * 48 + (lane >> 4) * 8 + (lane & 7)) * 128 + ((qch ^ (lane & 7)) << 4);
#pragma unroll
        for (int j = 0; j < 3; j++) stsm4t(oa + j * 2048, r[4 * j], r[4 * j + 1], r[4 * j + 2], r[4 * j + 3]);
        asm volatile("bar.sync %0, 128;" ::"r"(7 + wg) : "memory");
#pragma unroll
        for (int j = 0; j < 3; j++) {
            const int row = wg * 48 + j * 16 + wq * 4 + (lane >> 3);
            const uint4 v = lds128(A_OUT + row * 128 + (((lane ^ row) & 7) << 4));
            if (row < nrows) ((uint4*)out)[(cta * NPC + row) * 8 + (lane & 7)] = v;
        }
    }
    TS(14);
    if (__syncthreads_or(bad)) slow_path(smem_raw, x, ea, src, dst, w1, b1, w2, b2, out);
}

}

extern "C" void kernel_launch(void* const* d_in, const int* in_sizes, int n_in, void* d_out, int out_size) {
    typedef CUresult (*EncodeFn)(CUtensorMap*, CUtensorMapDataType, cuuint32_t, void*, const cuuint64_t*, const cuuint64_t*, const cuuint32_t*,
                                 const cuuint32_t*, CUtensorMapInterleave, CUtensorMapSwizzle, CUtensorMapL2promotion, CUtensorMapFloatOOBfill);
    static bool init = false;
    static EncodeFn encode = nullptr;
    static void* scratch = nullptr;
    if (!init) {
        cudaFuncSetAttribute(mpnn_kernel, cudaFuncAttributeMaxDynamicSharedMemorySize, SMEM_BYTES);
        void* fn = nullptr;
        cudaDriverEntryPointQueryResult st;
        if (cudaGetDriverEntryPoint("cuTensorMapEncodeTiled", &fn, cudaEnableDefault, &st) == cudaSuccess && st == cudaDriverEntryPointSuccess) encode = (EncodeFn)fn;
        if (cudaGetSymbolAddress(&scratch, g_scratch) != cudaSuccess) scratch = nullptr;
        init = true;
    }
    CUtensorMap map = {};
    const cuuint64_t dims[2] = {128, 144}, strides[1] = {256};
    const cuuint32_t box[2] = {64, 16}, estr[2] = {1, 1};
    const bool have_map = encode && encode(&map, CU_TENSOR_MAP_DATA_TYPE_BFLOAT16, 2, d_in[4], dims, strides, box, estr, CU_TENSOR_MAP_INTERLEAVE_NONE,
                                          CU_TENSOR_MAP_SWIZZLE_128B, CU_TENSOR_MAP_L2_PROMOTION_NONE, CU_TENSOR_MAP_FLOAT_OOB_FILL_NONE) == CUDA_SUCCESS;
    mpnn_kernel<<<NCTA, NT, SMEM_BYTES>>>((const __nv_bfloat16*)d_in[0], (const __nv_bfloat16*)d_in[1], (const int*)d_in[2], (const int*)d_in[3],
                                          (const __nv_bfloat16*)d_in[4], (const __nv_bfloat16*)d_in[5], (const __nv_bfloat16*)d_in[6],
                                          (const __nv_bfloat16*)d_in[7], (__nv_bfloat16*)d_out, have_map ? (Scratch*)scratch : nullptr, map);
}
```

```cpp
#include <cuda_runtime.h>
#include <cuda.h>
#include <cuda_bf16.h>
#include <cuda_fp16.h>
#include <stdint.h>

namespace {

constexpr int N_NODES = 25000;
constexpr int N_EDGES = 800000;
constexpr int NCTA = 132;
constexpr int NPC = 190;
constexpr int NT = 640;
constexpr int NP = 512;
constexpr int CHUNK = 6060;
constexpr int R = 8;
#define SFP 3
#define WP 1
constexpr int LMAX = 57;
constexpr int MINB = 127;
constexpr int CAP = 91;
constexpr int SPITCH = 368;
constexpr int GPITCH = 24;
constexpr int OVFCAP = 112;
constexpr uint32_t TAGMOD = (1u << 22) - 1;
constexpr uint32_t EMPTY = 0xff000000u;
constexpr int SPIN = 1 << 16;
#define MBSPIN (1 << 22)

constexpr uint32_t SB = 1024;
constexpr uint32_t A_XR = SB;
constexpr uint32_t A_ER = A_XR + R * 8192;
constexpr uint32_t A_SEL = A_ER + R * 2048;
constexpr uint32_t QP = 200 * 128;
constexpr uint32_t A_QH = A_SEL + R * 2048;
constexpr uint32_t A_TAB = A_QH + 2 * QP;
constexpr uint32_t A_CNT = A_TAB + 60 * 512;
constexpr uint32_t A_KEY = A_CNT + 136 * 4;
constexpr uint32_t A_EV = A_KEY + 224 * 4;
constexpr uint32_t A_MISC = A_EV + 128;
constexpr uint32_t A_ZEND = A_MISC + 16;
constexpr uint32_t A_TAG = A_ZEND;
constexpr uint32_t A_B1 = A_TAG + 16;
constexpr uint32_t A_B2 = A_B1 + 256;
constexpr uint32_t A_INFO = A_B2 + 128;
constexpr uint32_t A_BAR = A_INFO + 196 * 4;
constexpr uint32_t A_OVF = A_BAR + 18 * 8;
constexpr uint32_t A_SS = A_OVF + OVFCAP * 8;
constexpr uint32_t A_END = A_SS + 4 * 512;
constexpr int SMEM_BYTES = A_END - SB;
constexpr uint32_t A_STG = A_XR;
constexpr uint32_t A_WB = A_SEL;
constexpr uint32_t A_WA = A_XR + 49 * 1024;
constexpr uint32_t A_XO = A_TAB;
constexpr uint32_t A_W2 = A_TAB;
constexpr uint32_t A_OUT = A_XR;
static_assert(A_STG + (NCTA + 1) * SPITCH + 16 <= A_WA && A_WA + 2 * 10240 <= A_SEL && A_XO + 192 * 128 <= A_CNT && (2 * LMAX + 3) * 256 <= A_CNT - A_TAB, "alias");
static_assert(A_QH % 1024 == 0 && QP % 1024 == 0 && A_TAB % 1024 == 0 && A_WA % 1024 == 0 && A_SEL % 1024 == 0, "align");
static_assert(A_CNT % 16 == 0 && A_ZEND % 16 == 0 && A_B2 % 16 == 0 && A_B1 % 16 == 0 && A_BAR % 8 == 0 && A_KEY % 16 == 0 && A_INFO % 16 == 0 && A_MISC % 16 == 0 && A_SS % 16 == 0, "align");
static_assert(SMEM_BYTES <= 199680 && A_ZEND - A_CNT <= 2048, "smem");

struct Scratch {
    uint4 flag[NCTA * 40];
    uint32_t cnt, pad[31];
    uint4 x16[N_NODES * 8];
    uint4 ent[NCTA * NCTA * GPITCH];
};
__device__ __align__(128) Scratch g_scratch;

#define TL(i)
#define TC(i)
#define TV(i, v)
#define TS(i)
#define TW(i)
#define TWD(i, v)
#define TSX(i, cond)

__device__ __forceinline__ void wg_fence() { asm volatile("wgmma.fence.sync.aligned;" ::: "memory"); }
__device__ __forceinline__ void wg_commit() { asm volatile("wgmma.commit_group.sync.aligned;" ::: "memory"); }
__device__ __forceinline__ void wg_wait0() { asm volatile("wgmma.wait_group.sync.aligned 0;" ::: "memory"); }
__device__ __forceinline__ void wg_wait1() { asm volatile("wgmma.wait_group.sync.aligned 1;" ::: "memory"); }
template <int M> __device__ __forceinline__ void fence_regs(uint32_t (&d)[M]) {
#pragma unroll
    for (int i = 0; i < M; i++) asm volatile("" : "+r"(d[i])::"memory");
}
template <int M> __device__ __forceinline__ void fence_regs(float (&d)[M]) {
#pragma unroll
    for (int i = 0; i < M; i++) asm volatile("" : "+f"(d[i])::"memory");
}
constexpr uint32_t HI128 = 0x40000040;
constexpr uint32_t HI32 = 0xC0000010;
template <int SC, uint32_t HI>
__device__ __forceinline__ void mma64h(uint32_t (&d)[16], const uint32_t (&a)[4], uint32_t lo) {
    asm volatile("{\n.reg .pred p;\n.reg .b64 dsc;\nsetp.ne.b32 p, %21, 0;\nmov.b64 dsc, {%20, %22};\n"
        "wgmma.mma_async.sync.aligned.m64n64k16.f16.f16.f16 {%0, %1, %2, %3, %4, %5, %6, %7, %8, %9, %10, %11, %12, %13, %14, %15}, {%16, %17, %18, %19}, dsc, p, 1, 1, 0;\n}\n"
        : "+r"(d[0]), "+r"(d[1]), "+r"(d[2]), "+r"(d[3]), "+r"(d[4]), "+r"(d[5]), "+r"(d[6]), "+r"(d[7]), "+r"(d[8]), "+r"(d[9]), "+r"(d[10]), "+r"(d[11]), "+r"(d[12]), "+r"(d[13]), "+r"(d[14]), "+r"(d[15])
        : "r"(a[0]), "r"(a[1]), "r"(a[2]), "r"(a[3]), "r"(lo), "n"(SC), "n"(HI));
}
template <uint32_t HI>
__device__ __forceinline__ void mma64h0(uint32_t (&d)[16], const uint32_t (&a)[4], uint32_t lo) {
    asm volatile("{\n.reg .pred p;\n.reg .b64 dsc;\nsetp.ne.b32 p, 0, 0;\nmov.b64 dsc, {%20, %21};\n"
        "wgmma.mma_async.sync.aligned.m64n64k16.f16.f16.f16 {%0, %1, %2, %3, %4, %5, %6, %7, %8, %9, %10, %11, %12, %13, %14, %15}, {%16, %17, %18, %19}, dsc, p, 1, 1, 0;\n}\n"
        : "=r"(d[0]), "=r"(d[1]), "=r"(d[2]), "=r"(d[3]), "=r"(d[4]), "=r"(d[5]), "=r"(d[6]), "=r"(d[7]), "=r"(d[8]), "=r"(d[9]), "=r"(d[10]), "=r"(d[11]), "=r"(d[12]), "=r"(d[13]), "=r"(d[14]), "=r"(d[15])
        : "r"(a[0]), "r"(a[1]), "r"(a[2]), "r"(a[3]), "r"(lo), "n"(HI));
}
template <uint32_t HI>
__device__ __forceinline__ void mma16t(uint32_t (&d)[4], uint32_t a0, uint32_t a1, uint32_t a2, uint32_t a3, uint32_t lo) {
    asm volatile("{\n.reg .pred p;\n.reg .b64 dsc;\nsetp.eq.b32 p, 0, 0;\nmov.b64 dsc, {%8, %9};\n"
        "wgmma.mma_async.sync.aligned.m64n16k16.f16.f16.f16 {%0, %1, %2, %3}, {%4, %5, %6, %7}, dsc, p, 1, 1, 1;\n}\n"
        : "+r"(d[0]), "+r"(d[1]), "+r"(d[2]), "+r"(d[3]) : "r"(a0), "r"(a1), "r"(a2), "r"(a3), "r"(lo), "n"(HI));
}
template <int SC, uint32_t HI>
__device__ __forceinline__ void mma96h(uint32_t (&d)[24], const uint32_t (&a)[4], uint32_t lo) {
    asm volatile("{\n.reg .pred p;\n.reg .b64 dsc;\nsetp.ne.b32 p, %29, 0;\nmov.b64 dsc, {%28, %30};\n"
        "wgmma.mma_async.sync.aligned.m64n96k16.f16.f16.f16 {%0, %1, %2, %3, %4, %5, %6, %7, %8, %9, %10, %11, %12, %13, %14, %15, %16, %17, %18, %19, %20, %21, %22, %23}, {%24, %25, %26, %27}, dsc, p, 1, 1, 0;\n}\n"
        : "+r"(d[0]), "+r"(d[1]), "+r"(d[2]), "+r"(d[3]), "+r"(d[4]), "+r"(d[5]), "+r"(d[6]), "+r"(d[7]), "+r"(d[8]), "+r"(d[9]), "+r"(d[10]), "+r"(d[11]), "+r"(d[12]), "+r"(d[13]), "+r"(d[14]), "+r"(d[15]), "+r"(d[16]), "+r"(d[17]), "+r"(d[18]), "+r"(d[19]), "+r"(d[20]), "+r"(d[21]), "+r"(d[22]), "+r"(d[23])
        : "r"(a[0]), "r"(a[1]), "r"(a[2]), "r"(a[3]), "r"(lo), "n"(SC), "n"(HI));
}
template <int SC, uint32_t HI>
__device__ __forceinline__ void mma48f(float (&d)[24], const uint32_t (&a)[4], uint32_t lo) {
    asm volatile("{\n.reg .pred p;\n.reg .b64 dsc;\nsetp.ne.b32 p, %29, 0;\nmov.b64 dsc, {%28, %30};\n"
        "wgmma.mma_async.sync.aligned.m64n48k16.f32.f16.f16 {%0, %1, %2, %3, %4, %5, %6, %7, %8, %9, %10, %11, %12, %13, %14, %15, %16, %17, %18, %19, %20, %21, %22, %23}, {%24, %25, %26, %27}, dsc, p, 1, 1, 0;\n}\n"
        : "+f"(d[0]), "+f"(d[1]), "+f"(d[2]), "+f"(d[3]), "+f"(d[4]), "+f"(d[5]), "+f"(d[6]), "+f"(d[7]), "+f"(d[8]), "+f"(d[9]), "+f"(d[10]), "+f"(d[11]), "+f"(d[12]), "+f"(d[13]), "+f"(d[14]), "+f"(d[15]), "+f"(d[16]), "+f"(d[17]), "+f"(d[18]), "+f"(d[19]), "+f"(d[20]), "+f"(d[21]), "+f"(d[22]), "+f"(d[23])
        : "r"(a[0]), "r"(a[1]), "r"(a[2]), "r"(a[3]), "r"(lo), "n"(SC), "n"(HI));
}
__device__ __forceinline__ uint32_t hadd2(uint32_t a, uint32_t b) { uint32_t r; asm("add.rn.f16x2 %0, %1, %2;" : "=r"(r) : "r"(a), "r"(b)); return r; }
__device__ __forceinline__ uint32_t hfma2(uint32_t a, uint32_t b, uint32_t c) { uint32_t r; asm("fma.rn.f16x2 %0, %1, %2, %3;" : "=r"(r) : "r"(a), "r"(b), "r"(c)); return r; }
__device__ __forceinline__ uint32_t htanh2(uint32_t a) { uint32_t r; asm("tanh.approx.f16x2 %0, %1;" : "=r"(r) : "r"(a)); return r; }
__device__ __forceinline__ uint32_t pack_h2(float lo, float hi) { uint32_t r; asm("cvt.rn.f16x2.f32 %0, %1, %2;" : "=r"(r) : "f"(hi), "f"(lo)); return r; }
__device__ __forceinline__ uint32_t pack_b2(float lo, float hi) { uint32_t r; asm("cvt.rn.bf16x2.f32 %0, %1, %2;" : "=r"(r) : "f"(hi), "f"(lo)); return r; }
__device__ __forceinline__ uint32_t bf2h(uint32_t v) { return pack_h2(__uint_as_float(v << 16), __uint_as_float(v & 0xffff0000u)); }
__device__ __forceinline__ uint32_t bf2h_half(uint32_t v) { return pack_h2(0.5f * __uint_as_float(v << 16), 0.5f * __uint_as_float(v & 0xffff0000u)); }
__device__ __forceinline__ uint4 bf2h4(uint4 v) { return make_uint4(bf2h(v.x), bf2h(v.y), bf2h(v.z), bf2h(v.w)); }

__device__ __forceinline__ void cp16(uint32_t s, const void* g) { asm volatile("cp.async.cg.shared.global [%0], [%1], 16;" ::"r"(s), "l"(g) : "memory"); }
__device__ __forceinline__ void cp_commit() { asm volatile("cp.async.commit_group;" ::: "memory"); }
template <int N> __device__ __forceinline__ void cp_wait() { asm volatile("cp.async.wait_group %0;" ::"n"(N) : "memory"); }
__device__ __forceinline__ void bulk_g2s(uint32_t s, const void* g, uint32_t bytes, uint32_t bar) {
    asm volatile("cp.async.bulk.shared::cluster.global.mbarrier::complete_tx::bytes [%0], [%1], %2, [%3];" ::"r"(s), "l"(g), "r"(bytes), "r"(bar) : "memory");
}
__device__ __forceinline__ void tma_g2s(uint32_t s, const CUtensorMap* m, int c0, int c1, uint32_t bar) {
    asm volatile("cp.async.bulk.tensor.2d.shared::cluster.global.mbarrier::complete_tx::bytes [%0], [%1, {%2, %3}], [%4];" ::"r"(s), "l"(m), "r"(c0), "r"(c1), "r"(bar) : "memory");
}
__device__ __forceinline__ void l2_prefetch(const void* g, uint32_t bytes) { asm volatile("cp.async.bulk.prefetch.L2.global [%0], %1;" ::"l"(g), "r"(bytes) : "memory"); }
__device__ __forceinline__ void proxy_fence() { asm volatile("fence.proxy.async.shared::cta;" ::: "memory"); }
__device__ __forceinline__ bool mbar_try(uint32_t bar, uint32_t parity) {
    uint32_t ok;
    asm volatile("{\n.reg .pred p;\nmbarrier.try_wait.parity.shared::cta.b64 p, [%1], %2;\nselp.u32 %0, 1, 0, p;\n}" : "=r"(ok) : "r"(bar), "r"(parity) : "memory");
    return ok;
}
__device__ __forceinline__ void mbar_wait(uint32_t bar, uint32_t parity) {
    if (__builtin_expect(!mbar_try(bar, parity), 0))
        for (int it = 0; it < MBSPIN; it++) if (mbar_try(bar, parity)) break;
}
__device__ __forceinline__ void mbar_arrive(uint32_t bar) { asm volatile("mbarrier.arrive.shared::cta.b64 _, [%0];" ::"r"(bar) : "memory"); }
__device__ __forceinline__ uint32_t lds32(uint32_t a) { uint32_t r; asm volatile("ld.shared.u32 %0, [%1];" : "=r"(r) : "r"(a) : "memory"); return r; }
__device__ __forceinline__ uint32_t lds16(uint32_t a) { uint32_t r; asm volatile("ld.shared.u16 %0, [%1];" : "=r"(r) : "r"(a) : "memory"); return r; }
__device__ __forceinline__ uint2 lds64(uint32_t a) { uint2 r; asm volatile("ld.shared.v2.u32 {%0,%1}, [%2];" : "=r"(r.x), "=r"(r.y) : "r"(a) : "memory"); return r; }
__device__ __forceinline__ uint4 lds128(uint32_t a) { uint4 r; asm volatile("ld.shared.v4.u32 {%0,%1,%2,%3}, [%4];" : "=r"(r.x), "=r"(r.y), "=r"(r.z), "=r"(r.w) : "r"(a) : "memory"); return r; }
__device__ __forceinline__ void sts128(uint32_t a, uint4 v) { asm volatile("st.shared.v4.u32 [%0], {%1,%2,%3,%4};" ::"r"(a), "r"(v.x), "r"(v.y), "r"(v.z), "r"(v.w) : "memory"); }
__device__ __forceinline__ void sts64(uint32_t a, uint32_t x, uint32_t y) { asm volatile("st.shared.v2.u32 [%0], {%1,%2};" ::"r"(a), "r"(x), "r"(y) : "memory"); }
__device__ __forceinline__ void sts32(uint32_t a, uint32_t v) { asm volatile("st.shared.u32 [%0], %1;" ::"r"(a), "r"(v) : "memory"); }
__device__ __forceinline__ void sts16(uint32_t a, uint32_t v) { asm volatile("st.shared.u16 [%0], %1;" ::"r"(a), "r"(v) : "memory"); }
__device__ __forceinline__ void sts8(uint32_t a, uint32_t v) { asm volatile("st.shared.u8 [%0], %1;" ::"r"(a), "r"(v) : "memory"); }
__device__ __forceinline__ uint32_t atoms_inc(uint32_t a) { uint32_t r; asm volatile("atom.shared.add.u32 %0, [%1], 1;" : "=r"(r) : "r"(a) : "memory"); return r; }
__device__ __forceinline__ uint32_t ldg_rlx32(const void* p) { uint32_t r; asm volatile("ld.relaxed.gpu.global.u32 %0, [%1];" : "=r"(r) : "l"(p) : "memory"); return r; }
#define LDI "ld.relaxed.gpu.global.v2.u32"
__device__ __forceinline__ int2 ldg64(const void* p) { int2 r; asm volatile(LDI " {%0,%1}, [%2];" : "=r"(r.x), "=r"(r.y) : "l"(p) : "memory"); return r; }
__device__ __forceinline__ void ldg64_if(int2& r, const void* p, bool on) {
    asm volatile("{\n.reg .pred p;\nsetp.ne.u32 p, %3, 0;\n@p " LDI " {%0,%1}, [%2];\n}" : "+r"(r.x), "+r"(r.y) : "l"(p), "r"((uint32_t)on) : "memory");
}
__device__ __forceinline__ uint4 ldg_rlx128_if(const void* p, bool on) {
    uint4 r;
    asm volatile("{\n.reg .pred p;\n.reg .b64 a, b;\nsetp.ne.u32 p, %5, 0;\n@p ld.relaxed.gpu.global.v2.b64 {a, b}, [%4];\nmov.b64 {%0,%1}, a;\nmov.b64 {%2,%3}, b;\n}"
                 : "=r"(r.x), "=r"(r.y), "=r"(r.z), "=r"(r.w) : "l"(p), "r"((uint32_t)on) : "memory");
    return r;
}
__device__ __forceinline__ void ldg_rlx128_upd(uint64_t& a, uint64_t& b, const void* p, bool on) {
    asm volatile("{\n.reg .pred p;\nsetp.ne.u32 p, %3, 0;\n@p ld.relaxed.gpu.global.v2.b64 {%0, %1}, [%2];\n}" : "+l"(a), "+l"(b) : "l"(p), "r"((uint32_t)on) : "memory");
}
__device__ __forceinline__ uint2 ldg_rlx64_if(const void* p, bool on) {
    uint64_t a = 0;
    asm volatile("{\n.reg .pred p;\nsetp.ne.u32 p, %2, 0;\n@p ld.relaxed.gpu.global.b64 %0, [%1];\n}" : "+l"(a) : "l"(p), "r"((uint32_t)on) : "memory");
    return make_uint2((uint32_t)a, (uint32_t)(a >> 32));
}
__device__ __forceinline__ uint4 ldg_acq128(const void* p) {
    uint4 r;
    asm volatile("ld.acquire.gpu.global.v4.u32 {%0,%1,%2,%3}, [%4];" : "=r"(r.x), "=r"(r.y), "=r"(r.z), "=r"(r.w) : "l"(p) : "memory");
    return r;
}
__device__ __forceinline__ void stg_rlx32(void* p, uint32_t v) { asm volatile("st.relaxed.gpu.global.u32 [%0], %1;" ::"l"(p), "r"(v) : "memory"); }
__device__ __forceinline__ void stg_rlx128(void* p, uint4 v) {
    asm volatile("{\n.reg .b64 a, b;\nmov.b64 a, {%1,%2};\nmov.b64 b, {%3,%4};\nst.relaxed.gpu.global.v2.b64 [%0], {a, b};\n}" ::"l"(p), "r"(v.x), "r"(v.y), "r"(v.z), "r"(v.w) : "memory");
}
__device__ __forceinline__ void stg_rlx128_if(void* p, uint4 v, bool on) {
    asm volatile("{\n.reg .pred p;\n.reg .b64 a, b;\nsetp.ne.u32 p, %5, 0;\nmov.b64 a, {%1,%2};\nmov.b64 b, {%3,%4};\n@p st.relaxed.gpu.global.v2.b64 [%0], {a, b};\n}" ::"l"(p), "r"(v.x), "r"(v.y), "r"(v.z), "r"(v.w), "r"((uint32_t)on) : "memory");
}
__device__ __forceinline__ void ldsm4t(uint32_t (&r)[4], uint32_t a) {
    asm volatile("ldmatrix.sync.aligned.m8n8.x4.trans.shared.b16 {%0,%1,%2,%3}, [%4];" : "=r"(r[0]), "=r"(r[1]), "=r"(r[2]), "=r"(r[3]) : "r"(a) : "memory");
}
__device__ __forceinline__ void ldsm2t(uint32_t& r0, uint32_t& r1, uint32_t a) {
    asm volatile("ldmatrix.sync.aligned.m8n8.x2.trans.shared.b16 {%0,%1}, [%2];" : "=r"(r0), "=r"(r1) : "r"(a) : "memory");
}
__device__ __forceinline__ void stsm2t(uint32_t a, uint32_t r0, uint32_t r1) {
    asm volatile("stmatrix.sync.aligned.m8n8.x2.trans.shared.b16 [%0], {%1,%2};" ::"r"(a), "r"(r0), "r"(r1) : "memory");
}
__device__ __forceinline__ void stsm4t(uint32_t a, uint32_t r0, uint32_t r1, uint32_t r2, uint32_t r3) {
    asm volatile("stmatrix.sync.aligned.m8n8.x4.trans.shared.b16 [%0], {%1,%2,%3,%4};" ::"r"(a), "r"(r0), "r"(r1), "r"(r2), "r"(r3) : "memory");
}
template <int ID, int N> __device__ __forceinline__ void bar_sync() { asm volatile("bar.sync %0, %1;" ::"n"(ID), "n"(N) : "memory"); }
template <int ID, int N> __device__ __forceinline__ void bar_arrive() { asm volatile("bar.arrive %0, %1;" ::"n"(ID), "n"(N) : "memory"); }
__device__ __forceinline__ uint32_t scan_up(uint32_t v) {
#pragma unroll
    for (int o = 1; o < 32; o <<= 1)
        asm volatile("{\n.reg .pred p;\n.reg .u32 t;\nshfl.sync.up.b32 t|p, %0, %1, 0, -1;\n@p add.u32 %0, %0, t;\n}" : "+r"(v) : "r"(o));
    return v;
}
__device__ __forceinline__ float bf2f(const __nv_bfloat16* p) { return __bfloat162float(*p); }

__device__ __forceinline__ int chunk_start(int c) { return c * CHUNK + min(c, 40) * 2; }
static_assert(NCTA * CHUNK + 80 == N_EDGES && CHUNK / 2 + 1 <= 6 * NP && CHUNK / 2 >= 5 * NP, "chunks");

__device__ __noinline__ void slow_path(uint8_t* sp, const __nv_bfloat16* x, const __nv_bfloat16* ea, const int* src, const int* dst,
                                       const __nv_bfloat16* w1, const __nv_bfloat16* b1, const __nv_bfloat16* w2,
                                       const __nv_bfloat16* b2, __nv_bfloat16* out) {
    const int tid = threadIdx.x, lane = tid & 31, warp = tid >> 5, cta = blockIdx.x;
    const int nrows = min(NPC, N_NODES - cta * NPC);
    float* hs = (float*)sp;
    __nv_bfloat16* w1s = (__nv_bfloat16*)(sp + 192 * 128 * 4);
    int* dg = (int*)(sp + 192 * 128 * 4 + 144 * 128 * 2);
    __syncthreads();
    for (int i = tid; i < 192 * 128; i += NT) hs[i] = 0.f;
    for (int i = tid; i < 144 * 128; i += NT) w1s[i] = w1[i];
    for (int i = tid; i < 192; i += NT) dg[i] = 0;
    __syncthreads();
    float bb[4];
    for (int j = 0; j < 4; j++) bb[j] = bf2f(b1 + lane * 4 + j);
    for (int i0 = warp * 32; i0 < N_EDGES; i0 += NT) {
        const int mine = dst[i0 + lane] - cta * NPC;
        uint32_t hit = __ballot_sync(0xffffffffu, (unsigned)mine < (unsigned)nrows);
        while (hit) {
            const int b = __ffs(hit) - 1;
            hit &= hit - 1;
            const int eid = i0 + b, dl = __shfl_sync(0xffffffffu, mine, b), s = src[eid];
            float v[5];
            v[0] = bf2f(x + s * 64 + lane); v[1] = bf2f(x + s * 64 + 32 + lane);
            v[2] = bf2f(x + (cta * NPC + dl) * 64 + lane); v[3] = bf2f(x + (cta * NPC + dl) * 64 + 32 + lane);
            v[4] = lane < 16 ? bf2f(ea + (size_t)eid * 16 + lane) : 0.f;
            float z[4] = {bb[0], bb[1], bb[2], bb[3]};
#pragma unroll
            for (int c = 0; c < 5; c++) {
                for (int kk = 0; kk < (c == 4 ? 16 : 32); kk++) {
                    float a = __shfl_sync(0xffffffffu, v[c], kk);
                    const __nv_bfloat16* wr = w1s + (c * 32 + kk) * 128 + lane * 4;
#pragma unroll
                    for (int j = 0; j < 4; j++) z[j] = fmaf(a, __bfloat162float(wr[j]), z[j]);
                }
            }
#pragma unroll
            for (int j = 0; j < 4; j++) atomicAdd(&hs[dl * 128 + lane * 4 + j], z[j] / (1.f + expf(-z[j])));
            if (lane == 0) atomicAdd(&dg[dl], 1);
        }
    }
    __syncthreads();
    for (int i = tid; i < nrows * 64; i += NT) {
        int n = i >> 6, d = i & 63;
        float a = 0.f;
        if (dg[n] > 0) {
            a = (float)dg[n] * bf2f(b2 + d);
            for (int h = 0; h < 128; h++) a = fmaf(hs[n * 128 + h], bf2f(w2 + h * 64 + d), a);
        }
        out[(size_t)(cta * NPC + n) * 64 + d] = __float2bfloat16(a);
    }
}

__global__ void __launch_bounds__(NT, 1)
mpnn_kernel(const __nv_bfloat16* __restrict__ x, const __nv_bfloat16* __restrict__ ea, const int* __restrict__ src,
            const int* __restrict__ dst, const __nv_bfloat16* __restrict__ w1, const __nv_bfloat16* __restrict__ b1,
            const __nv_bfloat16* __restrict__ w2, const __nv_bfloat16* __restrict__ b2, __nv_bfloat16* __restrict__ out,
            Scratch* __restrict__ gs, const __grid_constant__ CUtensorMap w1map) {
    extern __shared__ uint8_t smem_raw[];
    const int tid = threadIdx.x, lane = tid & 31;
    __builtin_assume(tid < NT);
    const int warp = __shfl_sync(0xffffffffu, tid >> 5, 0);
    const int cta = blockIdx.x;
    const int nrows = min(NPC, N_NODES - cta * NPC);
    const int e0 = chunk_start(cta);
    const int nv2 = CHUNK / 2 + (cta < 40);
    if ((uint32_t)__cvta_generic_to_shared(smem_raw) != SB || !gs) { slow_path(smem_raw, x, ea, src, dst, w1, b1, w2, b2, out); return; }
    constexpr uint32_t bar_w = A_BAR + R * 16, bar_x = bar_w + 8;
    const int wg = warp >> 2, wq = warp & 3, hh = wg & 1, strm = wg >> 1;
    const uint32_t qch = wq * 2 + ((lane >> 3) & 1);
    const uint32_t wofs = (((lane >> 4) & 1) * 8 + (lane & 7)) * 128 + ((qch ^ (lane & 7)) << 4);
    int bad = 0;
    TS(0);

    int2 d2[6];
    const int pt = tid - NP;
    if (wg == 4) {
        uint32_t cnt0;
        if (pt == 64) cnt0 = ldg_rlx32(&gs->cnt);
        if (pt == 96) {
#pragma unroll
            for (int i = 0; i < 2 * R + 2; i++) asm volatile("mbarrier.init.shared::cta.b64 [%0], %1;" ::"r"(A_BAR + i * 8), "r"(i < R ? 2 : i < 2 * R ? 8 : 1) : "memory");
            proxy_fence();
            asm volatile("mbarrier.arrive.expect_tx.shared::cta.b64 _, [%0], %1;" ::"r"(bar_w), "r"(144 * 256 + 256 + 128) : "memory");
            asm volatile("mbarrier.arrive.expect_tx.shared::cta.b64 _, [%0], %1;" ::"r"(bar_x), "r"(nrows * 128) : "memory");
        }
        __syncwarp();
        {
            const uint32_t k = pt - (A_KEY - A_CNT) / 16, o = k < 56 ? 1u << 18 : 0u;
            if (pt < (int)(A_ZEND - A_CNT) / 16) sts128(A_CNT + pt * 16, make_uint4(4 * k * o, (4 * k + 1) * o, (4 * k + 2) * o, (4 * k + 3) * o));
        }
        if (pt == 64) {
            const uint32_t tag = cnt0 / NCTA + 1;
            sts64(A_TAG, tag << 21, tag >> 11 << 21);
            sts32(A_INFO + 192 * 4, A_TAG + 8 - A_TAB - (192u << 20));
        }
    } else {
        const int2* dp = (const int2*)(dst + e0) + tid;
        d2[5] = make_int2(NCTA * NPC, NCTA * NPC);
#pragma unroll
        for (int r = 0; r < 5; r++) d2[r] = ldg64(dp + r * NP);
        ldg64_if(d2[5], dp + 5 * NP, tid < nv2 - 5 * NP);
        stg_rlx128_if(gs->ent + ((tid >> 1) * NCTA + cta) * GPITCH + (lane & 1), make_uint4(0, 0, 0, 0), tid < 2 * NCTA);
    }
    __syncthreads();
    const uint2 tag = lds64(A_TAG);
    if (wg == 4) {
        const uint32_t tagw = tag.x | tag.y >> 11;
        if (warp == 19) {
            if (lane == 0) {
                bulk_g2s(A_XO, x + cta * NPC * 64, nrows * 128, bar_x);
                asm volatile("red.relaxed.gpu.global.inc.u32 [%0], %1;" ::"l"(&gs->cnt), "r"(NCTA * TAGMOD - 1) : "memory");
            }
            TSX(15, lane == 0);
            __syncwarp();
            if (lane < 18) {
                int i = lane + cta % 18;
                i = i >= 18 ? i - 18 : i;
                const int h = i & 1, rb = i >> 1;
                tma_g2s(rb >= 4 && rb < 8 ? A_WB + h * 8192 + (rb - 4) * 2048 : A_WA + h * 10240 + min(rb, 4) * 2048, &w1map, h * 64, rb * 16, bar_w);
            } else if (lane < 20) bulk_g2s(lane == 18 ? A_B1 : A_B2, lane == 18 ? b1 : b2, lane == 18 ? 256 : 128, bar_w);
            else if (lane == 20) l2_prefetch(w2, 128 * 64 * 2);
            __syncwarp();
        }
        mbar_wait(bar_x, 0);
        TW(0);
        const uint32_t xo = A_XO + (pt >> 3) * 128 + (((pt ^ (pt >> 3)) & 7) << 4);
        {
            uint4 xr[12];
#pragma unroll
            for (int r = 0; r < 12; r++) xr[r] = lds128(A_XO + (r * 128 + pt) * 16);
            __syncwarp();
#pragma unroll
            for (int r = 0; r < 12; r++) {
                const bool in = r * 128 + pt < nrows * 8;
                const uint4 v = in ? bf2h4(xr[r]) : make_uint4(0, 0, 0, 0);
                sts128(xo + r * 2048, v);
                if (in) gs->x16[cta * NPC * 8 + r * 128 + pt] = v;
            }
        }
        proxy_fence();
        mbar_wait(bar_w, 0);
        bar_sync<4, 128>();
        TW(1);
        if (warp == 19) {
            asm volatile("fence.acq_rel.gpu;" ::: "memory");
#pragma unroll
            for (int j = 0; j < 5; j++)
                if (j * 32 + lane < NCTA) stg_rlx32((uint32_t*)(gs->flag + (j * 32 + lane) * 40) + cta, tagw);
            TSX(16, lane == 0);
            __syncwarp();
        }
#pragma unroll 1
        for (int h = 0; h < 2; h++) {
            uint32_t wb[4][4], acc[2][24];
#pragma unroll
            for (int i = 0; i < 4; i++) ldsm4t(wb[i], A_WB + h * 8192 + wofs + i * 2048);
            const uint32_t bl0 = lds16(A_B1 + (h * 64 + wq * 16 + (lane >> 2)) * 2), bl1 = lds16(A_B1 + (h * 64 + wq * 16 + 8 + (lane >> 2)) * 2);
#pragma unroll
            for (int i = 0; i < 4; i++)
#pragma unroll
                for (int j = 0; j < 4; j++) wb[i][j] = bf2h_half(wb[i][j]);
            const uint32_t bq0 = bf2h_half(bl0 * 0x10001u), bq1 = bf2h_half(bl1 * 0x10001u);
#pragma unroll
            for (int i = 0; i < 4; i++) fence_regs(wb[i]);
            wg_fence();
#pragma unroll
            for (int n = 0; n < 2; n++) {
                const uint32_t lo = ((A_XO >> 4) | 0x10000) + n * 768;
                mma96h<0, HI128>(acc[n], wb[0], lo);
                mma96h<1, HI128>(acc[n], wb[1], lo + 2);
                mma96h<1, HI128>(acc[n], wb[2], lo + 4);
                mma96h<1, HI128>(acc[n], wb[3], lo + 6);
            }
            wg_commit();
            wg_wait0();
            fence_regs(acc[0]); fence_regs(acc[1]);
#pragma unroll
            for (int n = 0; n < 2; n++)
#pragma unroll
                for (int j = 0; j < 6; j++)
                    stsm4t(A_QH + h * QP + n * 12288 + wofs + j * 2048, hadd2(acc[n][4 * j], bq0), hadd2(acc[n][4 * j + 1], bq1), hadd2(acc[n][4 * j + 2], bq0), hadd2(acc[n][4 * j + 3], bq1));
        }
        if (pt == 64) l2_prefetch(src + cta * 6064, min(6064, N_EDGES - cta * 6064) * 4);
        bar_sync<4, 128>();
#pragma unroll 5
        for (int r = 0; r < 15; r++) sts128(A_TAB + (r * 128 + pt) * 16, make_uint4(EMPTY, EMPTY, EMPTY, EMPTY));
        bar_arrive<12, NT>();
        TW(2);
        const int par = wq >> 1, hf = wq & 1, gq = lane >> 3, cp = (lane >> 1) & 3;
        const uint32_t sel = A_SEL + hf * 2048 + (par * 32 + lane) * 32 + ((lane >> 2) & 1) * 16;
#pragma unroll
        for (int r = 0; r < 8; r++) sts128(A_SEL + hf * 2048 + par * 1024 + (r >> 1) * 4096 + (r & 1) * 512 + lane * 16, make_uint4(0, 0, 0, 0));
        if (warp == 19) {
            bool ok = false;
            for (int it = 0; it < SPIN && !ok; it++) {
                const uint4 f0 = ldg_acq128(gs->flag + cta * 40 + lane), f1 = ldg_acq128(gs->flag + cta * 40 + 32);
                ok = __all_sync(0xffffffffu, f0.x == tagw && f0.y == tagw && f0.z == tagw && f0.w == tagw && f1.x == tagw && f1.y == tagw && f1.z == tagw && f1.w == tagw);
            }
            bad = !ok;
            TSX(17, lane == 0);
        }
        const uint32_t bar_full = A_BAR + hf * 8, bar_empty = bar_full + R * 8;
        uint32_t xd[8];
#pragma unroll
        for (int c = 0; c < 8; c++) xd[c] = A_XR + hf * 8192 + (par * 32 + gq * 8) * 128 + (((lane & 7) ^ c) << 4);
        fence_regs(xd);
        uint32_t ed0 = A_ER + hf * 2048 + (par * 32 + gq * 8 + cp) * 32 + (lane & 1) * 16, ed1 = (ed0 ^ 16) + 128;
        const uint32_t sw = A_SS + wq * 128 + lane * 4, sr = A_SS + wq * 128 + gq * 32;
        const char* xg = (const char*)gs->x16 + (lane & 7) * 16;
        const char* eg = (const char*)ea + (lane & 1) * 16;
        const char* sp = (const char*)src;
        asm volatile("" : "+l"(xg), "+l"(eg), "+l"(sp), "+r"(ed0), "+r"(ed1));
        uint32_t prev[4] = {sel, sel, sel, sel};
        bar_sync<5, NT>();
        TSX(9, tid == 512);
        const uint4 ms = lds128(A_MISC);
        if (!ms.y) {
            const int L = hf ? ms.w >> 8 : ms.z;
            uint32_t tl = A_TAB + hf * ms.z * 256 + par * 128 + lane * 4, te = tl - lane * 4 + gq * 32 + cp * 4;
            auto finish = [&](int u, int off) {
                const uint32_t en = lds32(tl + off);
                const uint4 v0 = lds128(ed0 + u * 4096), v1 = lds128(ed1 + u * 4096);
                sts16(prev[u] + u * 4096, 0);
                prev[u] = sel ^ ((en >> 23) & 0x1e);
                sts16(prev[u] + u * 4096, en < (192u << 24) ? 0x3c00 : 0);
                sts128(ed0 + u * 4096, bf2h4(v0));
                sts128(ed1 + u * 4096, bf2h4(v1));
                proxy_fence();
                __syncwarp();
                if (lane == 0) mbar_arrive(bar_full + u * 16);
            };
            auto issue_e = [&](int st, uint32_t e0, uint32_t e1) {
                cp16(ed0 + st * 4096, eg + (size_t)(e0 & 0xfffff) * 32);
                cp16(ed1 + st * 4096, eg + (size_t)(e1 & 0xfffff) * 32);
            };
            auto issue_x = [&](int st, const uint4& a0, const uint4& a1) {
                const uint32_t a[8] = {a0.x, a0.y, a0.z, a0.w, a1.x, a1.y, a1.z, a1.w};
#pragma unroll
                for (int i = 0; i < 8; i++) cp16(xd[i] + st * 16384 + i * 128, xg + (size_t)a[i] * 128);
            };
            auto fetch_src = [&](int slot, uint32_t e) {
                asm volatile("cp.async.ca.shared.global [%0], [%1], 4;" ::"r"(sw + slot * 512), "l"(sp + (size_t)(e & 0xfffff) * 4) : "memory");
            };
            {
                uint32_t es[6], ee[6];
#pragma unroll
                for (int t = 0; t < 6; t++) es[t] = lds32(tl + t * 256);
#pragma unroll
                for (int t = 0; t < 6; t++) ee[t] = lds32(te + (t >> 1) * 256 + (t & 1) * 16);
                fetch_src(0, es[0]);
                cp_commit();
                issue_e(0, ee[0], ee[1]);
                cp_commit();
                fetch_src(1, es[1]);
                fetch_src(2, es[2]);
                cp_commit();
                cp_wait<2>();
                __syncwarp();
                issue_x(0, lds128(sr), lds128(sr + 16));
                fetch_src(3, es[3]);
                cp_commit();
                TW(4);
                cp_wait<1>();
                __syncwarp();
#pragma unroll
                for (int t = 1; t < 3; t++) {
                    const uint4 a0 = lds128(sr + t * 512), a1 = lds128(sr + t * 512 + 16);
                    issue_e(t, ee[2 * t], ee[2 * t + 1]);
                    issue_x(t, a0, a1);
                    fetch_src(t - 1, es[t + 3]);
                    cp_commit();
                }
            }
            cp_wait<2>();
            TW(5);
            finish(0, 0);
            TW(6);
            uint32_t ph = 1;
            for (int j = L;; j -= 4) {
#pragma unroll
                for (int u = 1; u < 5; u++) {
                    if (j == u) goto done;
                    if (u == 2) ph ^= 1;
                    const int st = (u + 2) & 3, off = (u + 2) * 256;
                    if (j > u + 2) {
                        const uint32_t es = lds32(tl + off + 768);
                        const uint4 a0 = lds128(sr + st * 512), a1 = lds128(sr + st * 512 + 16);
                        const uint32_t e0 = lds32(te + off), e1 = lds32(te + off + 16);
                        fetch_src((st + 3) & 3, es);
                        mbar_wait(bar_empty + st * 16, ph);
                        issue_e(st, e0, e1);
                        issue_x(st, a0, a1);
                    } else mbar_wait(bar_empty + st * 16, ph);
                    cp_commit();
                    cp_wait<2>();
                    finish(u & 3, u * 256);
                }
                tl += 1024; te += 1024;
            }
        done:
            if (lane == 0) mbar_arrive(bar_full + (L & 3) * 16);
            TSX(18, tid == 512);
            uint4 v[8];
#pragma unroll
            for (int i = 0; i < 8; i++) v[i] = __ldg((const uint4*)w2 + i * 128 + pt);
            cp_wait<0>();
            bar_sync<4, 128>();
#pragma unroll
            for (int i = 0; i < 8; i++) sts128(A_W2 + (i * 16 + (pt >> 3)) * 144 + (pt & 7) * 16, bf2h4(v[i]));
            bar_arrive<3, NT>();
        } else bad = 1;
    } else {
        TS(1);
        const uint32_t ja = tag.x + 192 + lane, jb = tag.y + 192 + lane;
        const int nr = warp < NCTA / 2 - 64 ? 5 : 4, half = lane >> 4;
        {
            uint32_t c[12], rk[12];
#pragma unroll
            for (int i = 0; i < 12; i++) {
                c[i] = __umulhi(i & 1 ? d2[i >> 1].y : d2[i >> 1].x, 44151u << 9);
                rk[i] = atoms_inc(A_CNT + c[i] * 4);
            }
            TS(2);
            const uint32_t tb = tag.y + (tid << 9), td = tag.x - tag.y;
#pragma unroll
            for (int i = 0; i < 12; i++)
                sts32(A_STG + 4 + c[i] * SPITCH + min(rk[i], (uint32_t)CAP) * 4,
                      (i & 1 ? d2[i >> 1].y : d2[i >> 1].x) + tb + (((i >> 1) * NP * 2 + (i & 1)) << 8) - c[i] * NPC + (rk[i] & 1) * td);
        }
        bar_sync<1, NP>();
        TS(3);
        {
            const uint32_t row = warp * 2 + half, p0 = (lane & 15) * 4;
            uint4* gp = gs->ent + (row * NCTA + cta) * GPITCH + (lane & 15);
            const uint32_t sp = A_STG + row * SPITCH + (lane & 15) * 16;
            uint32_t n[5];
            uint4 v[5];
#pragma unroll
            for (int k = 0; k < 5; k++) {
                n[k] = lds32(A_CNT + min(row + k * 32, NCTA + 1) * 4);
                v[k] = lds128(sp + k * 32 * SPITCH);
            }
            uint32_t big = 0;
#pragma unroll
            for (int k = 0; k < 5; k++) {
                if (p0 - 1 >= n[k]) v[k].x = p0 ? ja : ja + (n[k] << 8);
                if (p0 + 1 > n[k]) v[k].y = jb;
                if (p0 + 2 > n[k]) v[k].z = ja;
                if (p0 + 3 > n[k]) v[k].w = jb;
                stg_rlx128_if(gp + k * 32 * NCTA * GPITCH, v[k], (p0 & ~7u) <= n[k] && (k < 4 || nr == 5));
                if (n[k] >= 64 && (k < 4 || nr == 5)) big |= 1u << k;
            }
            while (__builtin_expect(big != 0, 0)) {
                const int k = __ffs(big) - 1;
                big &= big - 1;
                const uint32_t m = lds32(A_CNT + (row + k * 32) * 4), p = p0 + 64;
                if (p0 < 32 && (p & ~7u) <= m) {
                    uint4 u = lds128(sp + k * 32 * SPITCH + 256);
                    if (p > m) u.x = ja;
                    if (p + 1 > m) u.y = jb;
                    if (p + 2 > m) u.z = ja;
                    if (p + 3 > m) u.w = jb;
                    stg_rlx128(gp + k * 32 * NCTA * GPITCH + 16, u);
                }
            }
            __syncwarp();
        }
        TS(4); TW(0);
        uint32_t w[5][4];
        auto load_w = [&]() {
            mbar_wait(bar_w, 0);
#pragma unroll
            for (int i = 0; i < 5; i++) ldsm4t(w[i], A_WA + hh * 10240 + wofs + i * 2048);
#pragma unroll
            for (int i = 0; i < 5; i++) {
#pragma unroll
                for (int j = 0; j < 4; j++) w[i][j] = bf2h_half(w[i][j]);
                fence_regs(w[i]);
            }
        };
        TS(5);
        const uint4* rp = gs->ent + (cta * NCTA + warp * 2) * GPITCH;
        const uint4* hp = rp + (min(lane >> 1, 4) * 32 + (lane & 1)) * GPITCH;
        rp += half * GPITCH + (lane & 15);
        uint64_t en[10];
        uint32_t rk[20];
#pragma unroll
        for (int i = 0; i < 10; i++) en[i] = ja | (uint64_t)jb << 32;
        int nl = -1;
        bool fail = false;
        uint32_t pend = (1u << 2 * nr) - 1, todo = (1u << nr) - 1, got = 0;
        for (int it = 0;; it++) {
            const uint2 h = ldg_rlx64_if(hp, (pend >> lane) & 1);
            uint32_t next = 0;
#pragma unroll
            for (int k = 0; k < 5; k++) {
                if (got & (1u << k)) {
                    const uint32_t a = en[2 * k], b = en[2 * k] >> 32, c = en[2 * k + 1], d = en[2 * k + 1] >> 32;
                    if (__builtin_expect(__any_sync(0xffffffffu, ((a ^ tag.x) | (b ^ tag.y) | (c ^ tag.x) | (d ^ tag.y)) >= (1u << 21)), 0)) next |= 1u << k;
                    else {
                        rk[4 * k] = atoms_inc(A_KEY + (a & 255) * 4);
                        rk[4 * k + 1] = atoms_inc(A_KEY + (b & 255) * 4);
                        rk[4 * k + 2] = atoms_inc(A_KEY + (c & 255) * 4);
                        rk[4 * k + 3] = atoms_inc(A_KEY + (d & 255) * 4);
                    }
                }
            }
            const bool ok = ((h.x ^ tag.x) | (h.y ^ tag.y)) < (1u << 21) && ((pend >> lane) & 1);
            if (ok) nl = (h.x >> 8) & 0x1fff;
            if (ok && nl > CAP) { fail = true; nl = -1; }
            pend &= ~__ballot_sync(0xffffffffu, ok);
            uint32_t seen = 0;
#pragma unroll
            for (int k = 0; k < 5; k++) if (!(pend & (3u << 2 * k))) seen |= 1u << k;
            seen &= todo;
            todo &= ~seen;
            got = next | seen;
            if (!(got | todo)) break;
            if (it >= SPIN) { fail = true; nl = -1; break; }
            if (got) {
#pragma unroll
                for (int k = 0; k < 5; k++) ldg_rlx128_upd(en[2 * k], en[2 * k + 1], rp + k * 32 * GPITCH, (got & (1u << k)) && (lane & 15) * 4 <= __shfl_sync(0xffffffffu, nl, 2 * k + half));
            }
        }
        TW(2);
        uint32_t big = __ballot_sync(0xffffffffu, nl >= 64);
        while (__builtin_expect(big != 0, 0)) {
            const int k = __ffs(big) - 1;
            big &= big - 1;
            const int n = __shfl_sync(0xffffffffu, nl, k), row = (k >> 1) * 32 + warp * 2 + (k & 1);
            if (64 + 4 * lane <= n) {
                uint4 ex;
                bool bad = true;
                for (int it = 0; it < SPIN; it++) {
                    ex = ldg_rlx128_if(gs->ent + (cta * NCTA + row) * GPITCH + 16 + lane, true);
                    bad = ((ex.x ^ tag.x) | (ex.y ^ tag.y) | (ex.z ^ tag.x) | (ex.w ^ tag.y)) >= (1u << 21);
                    if (!bad) break;
                }
                if (bad) fail = true;
                else {
#pragma unroll
                    for (int j = 0; j < 4; j++) {
                        const uint32_t a = j == 0 ? ex.x : j == 1 ? ex.y : j == 2 ? ex.z : ex.w;
                        if (64 + 4 * lane + j <= n) {
                            const uint32_t r = atoms_inc(A_KEY + (a & 255) * 4), o = atoms_inc(A_MISC);
                            if (o < OVFCAP) sts64(A_OVF + o * 8, (a << 24) + ((a >> 8) & 0x1fff) + chunk_start(row), r);
                        }
                    }
                }
            }
            __syncwarp();
        }
        TW(3);
        if (fail) sts32(A_MISC + 4, 1);
        load_w();
        bar_sync<12, NT>();
        TS(7);
        const int nb = (nrows + 7) >> 3;
        int L, B0;
        uint32_t novf;
        {
            const uint4 k0 = lds128(A_KEY + min(lane, 23) * 32), k1 = lds128(A_KEY + min(lane, 23) * 32 + 16);
            const uint2 ms = lds64(A_MISC);
            const uint32_t k[8] = {k0.x, k0.y, k0.z, k0.w, k1.x, k1.y, k1.z, k1.w};
            uint32_t c[8], t = 0;
#pragma unroll
            for (int i = 0; i < 8; i++) { t += k[i] & 0xffff; c[i] = (t - k[i]) * 4; }
            const uint32_t len = lane < nb ? max(t, (uint32_t)MINB) : 0u, end = scan_up(len), start = end - len;
            if (lane < 24) {
                sts128(A_INFO + lane * 32, make_uint4(c[0] + start * 4, c[1] + start * 4, c[2] + start * 4, c[3] + start * 4));
                sts128(A_INFO + lane * 32 + 16, make_uint4(c[4] + start * 4, c[5] + start * 4, c[6] + start * 4, c[7] + start * 4));
            }
            const uint32_t total = __shfl_sync(0xffffffffu, end, 31);
            L = (total + 127) >> 7;
            B0 = __popc(__ballot_sync(0xffffffffu, end <= 64u * L));
            const int L1 = ((total + 63) >> 6) - L;
            novf = ms.x;
            fail = ms.y || L > LMAX || novf > OVFCAP;
            if (!fail && lane < nb && (lane < 2 || lane != B0 + 1))
                sts8(lane < 2 ? A_EV + (lane ? 64 + L1 : L) : A_EV - 1 + (start >> 6) + (lane > B0 ? 64 - L : 0), lane < 2 ? 255 : lane == B0 + 2 ? lane + 32 : lane);
            if (lane == 0) { sts32(A_MISC + 4, fail); sts64(A_MISC + 8, L, L1 << 8 | B0); }
            __syncwarp();
        }
        TS(8);
        if (!fail) {
#pragma unroll
            for (int i = 0; i < 20; i++)
                if (i < 16 || nr == 5) {
                    const uint32_t r = min(rk[i], 192u << 18);
                    rk[i] = lds32(A_INFO + (r >> 16)) + r * 4;
                }
#pragma unroll
            for (int i = 0; i < 20; i++)
                if (i < 16 || nr == 5) {
                    const uint32_t e = en[i >> 1] >> (i & 1) * 32, cs = chunk_start((i >> 2) * 32 + warp * 2 + half) - ((i & 1 ? tag.y : tag.x) >> 8);
                    sts32(A_TAB + rk[i], __funnelshift_r(e, e, 8) + cs);
                }
            if ((uint32_t)tid < novf) {
                const uint2 t = lds64(A_OVF + tid * 8);
                sts32(A_TAB + lds32(A_INFO + (t.y >> 16)) + t.y * 4, t.x);
            }
        }
        TW(6);
        bar_arrive<5, NT>();
        if (!fail) {
        const uint32_t qb = A_QH + hh * QP + (lane & 7) * 128 + ((qch ^ (lane & 7)) << 4);
        uint32_t acc[2][16], h[16], q[4], s[4], tt[WP];
        {
            const int first = strm ? B0 : 0;
            ldsm4t(q, qb + min(lane < 16 ? (first + 1) & ~1 : first | 1, 23) * 1024);
        }
        TS(10);
#pragma unroll
        for (int i = 0; i < 4; i++) s[i] = 0;
#pragma unroll
        for (int i = 0; i < 5; i++) fence_regs(w[i]);
        fence_regs(q); fence_regs(s);
        uint32_t eva = A_EV + strm * 64, clk = 0;
        const uint32_t lox = ((A_XR >> 4) | 0x10000) + strm * 512, loe = ((A_ER >> 4) | 0x10000) + strm * 128, los = ((A_SEL >> 4) | 0x10000) + strm * 128;
        const uint32_t bar_full = A_BAR + strm * 8, bar_empty = bar_full + R * 8;
        auto gemm = [&](int st, uint32_t ph, uint32_t (&d)[16]) {
            mbar_wait(bar_full + st * 16, ph);
            wg_fence();
            mma64h0<HI128>(d, w[0], lox + st * 1024);
            mma64h<1, HI128>(d, w[1], lox + st * 1024 + 2);
            mma64h<1, HI128>(d, w[2], lox + st * 1024 + 4);
            mma64h<1, HI128>(d, w[3], lox + st * 1024 + 6);
            mma64h<1, HI32>(d, w[4], loe + st * 256);
            mma64h<1, HI32>(d, q, los + st * 256);
            wg_commit();
        };
        uint32_t ph = 0;
        gemm(0, 0, acc[0]);
        TS(11); TC(21);
        wg_wait0();
        fence_regs(acc[0]);
        if (lane == 0) mbar_arrive(bar_empty);
#pragma unroll
        for (int i = 0; i < WP; i++) tt[i] = htanh2(acc[0][i]);
        for (;;) {
            TL(((eva - A_EV) >> 2) & 15);
            const uint32_t evw = lds32(eva);
#pragma unroll
            for (int st = 0; st < 4; st++) {
                const uint32_t ev = (evw >> (8 * st)) & 255;
                if (__builtin_expect(ev != 0, 0)) {
                    if (ev == 255) goto finished;
                    const uint32_t qa = qb + (ev & 31) * 1024, fa = ev & 32 ? qb + 24 * 1024 : qa - 2048;
                    if (ev & 1) { stsm2t(fa, s[2], s[3]); ldsm2t(q[2], q[3], qa); s[2] = 0; s[3] = 0; }
                    else { stsm2t(fa, s[0], s[1]); ldsm2t(q[0], q[1], qa); s[0] = 0; s[1] = 0; }
                    fence_regs(s); fence_regs(q);
                }
                uint32_t (&u)[16] = acc[st & 1];
                uint32_t (&v)[16] = acc[(st + 1) & 1];
                if (st == 3) ph ^= 1;
                gemm((st + 1) & 3, ph, v);
#pragma unroll
                for (int i = 0; i < 16; i++) {
                    if (i == SFP) { fence_regs(h); asm volatile("mov.u32 %0, %%clock;" : "=r"(clk)::"memory"); fence_regs(u); }
                    h[i] = hfma2(u[i], i < WP ? tt[i] : htanh2(u[i]), u[i]);
                }
                wg_fence();
#pragma unroll
                for (int k = 0; k < 4; k++) mma16t<HI32>(s, h[4 * k], h[4 * k + 1], h[4 * k + 2], h[4 * k + 3], los + st * 256 + k * 32);
                wg_commit();
                wg_wait1();
                fence_regs(v);
                if (lane == 0) mbar_arrive(bar_empty + ((st + 1) & 3) * 16);
#pragma unroll
                for (int i = 0; i < WP; i++) { tt[i] = htanh2(v[i]); asm volatile("" : "+r"(tt[i])::"memory"); }
                wg_wait0();
                fence_regs(s);
            }
            eva += 4;
        }
    finished:
        TS(12); TC(22);
        {
            const uint2 ms = lds64(A_MISC + 4 + 4);
            const int b0 = ms.y & 255, last = strm ? ((nrows + 7) >> 3) - 1 : b0;
            const bool odd = last & 1;
            uint32_t l0 = odd ? s[2] : s[0], l1 = odd ? s[3] : s[1];
            if (last > (strm ? b0 : 0)) stsm2t(qb + (strm && last - 1 == b0 ? 24 : last - 1) * 1024, odd ? s[0] : s[2], odd ? s[1] : s[3]);
            if (strm) stsm2t(qb + (last == b0 ? 24 : last) * 1024, l0, l1);
            bar_sync<3, NT>();
            if (!strm) {
                uint32_t a0, a1;
                ldsm2t(a0, a1, qb + 24 * 1024);
                stsm2t(qb + b0 * 1024, hadd2(l0, a0), hadd2(l1, a1));
            }
            bad = clk & ms.x >> 8;
        }
        proxy_fence();
        uint32_t a2[8][4];
        const uint32_t wa = A_W2 + (((lane >> 4) & 1) * 8 + (lane & 7)) * 144 + qch * 16;
#pragma unroll
        for (int i = 0; i < 8; i++) ldsm4t(a2[i], wa + i * 16 * 144);
        const float bo0 = __uint_as_float(lds16(A_B2 + (wq * 16 + (lane >> 2)) * 2) << 16);
        const float bo1 = __uint_as_float(lds16(A_B2 + (wq * 16 + 8 + (lane >> 2)) * 2) << 16);
        float d[24];
#pragma unroll
        for (int i = 0; i < 8; i++) fence_regs(a2[i]);
        bar_sync<6, 512>();
        TS(13);
        const uint32_t lo = ((A_QH >> 4) | 0x10000) + wg * 384;
        wg_fence();
        mma48f<0, HI128>(d, a2[0], lo);
#pragma unroll
        for (int i = 1; i < 8; i++) mma48f<1, HI128>(d, a2[i], lo + (i >> 2) * (QP / 16) + (i & 3) * 2);
        wg_commit();
        float dg[12];
#pragma unroll
        for (int j = 0; j < 6; j++) {
            const uint2 v = lds64(A_KEY + (wg * 48 + j * 8 + (lane & 3) * 2) * 4);
            dg[2 * j] = (float)(v.x & 0xffff); dg[2 * j + 1] = (float)(v.y & 0xffff);
        }
        wg_wait0();
        fence_regs(d);
        uint32_t r[12];
#pragma unroll
        for (int j = 0; j < 6; j++) {
            const float g0 = dg[2 * j], g1 = dg[2 * j + 1];
            const float v0 = g0 > 0.f ? fmaf(g0, bo0, d[4 * j]) : 0.f, v1 = g1 > 0.f ? fmaf(g1, bo0, d[4 * j + 1]) : 0.f;
            const float v2 = g0 > 0.f ? fmaf(g0, bo1, d[4 * j + 2]) : 0.f, v3 = g1 > 0.f ? fmaf(g1, bo1, d[4 * j + 3]) : 0.f;
            bad |= !(fabsf(v0) + fabsf(v1) + fabsf(v2) + fabsf(v3) < 3.0e38f);
            r[2 * j] = pack_b2(v0, v1); r[2 * j + 1] = pack_b2(v2, v3);
        }
        const uint32_t oa = A_OUT + (wg * 48 + (lane >> 4) * 8 + (lane & 7)) * 128 + ((qch ^ (lane & 7)) << 4);
#pragma unroll
        for (int j = 0; j < 3; j++) stsm4t(oa + j * 2048, r[4 * j], r[4 * j + 1], r[4 * j + 2], r[4 * j + 3]);
        asm volatile("bar.sync %0, 128;" ::"r"(7 + wg) : "memory");
#pragma unroll
        for (int j = 0; j < 3; j++) {
            const int row = wg * 48 + j * 16 + wq * 4 + (lane >> 3);
            const uint4 v = lds128(A_OUT + row * 128 + (((lane ^ row) & 7) << 4));
            if (row < nrows) ((uint4*)out)[(cta * NPC + row) * 8 + (lane & 7)] = v;
        }
        } else bad = 1;
    }
    TS(14);
    if (__syncthreads_or(bad)) slow_path(smem_raw, x, ea, src, dst, w1, b1, w2, b2, out);
}

}

extern "C" void kernel_launch(void* const* d_in, const int* in_sizes, int n_in, void* d_out, int out_size) {
    typedef CUresult (*EncodeFn)(CUtensorMap*, CUtensorMapDataType, cuuint32_t, void*, const cuuint64_t*, const cuuint64_t*, const cuuint32_t*,
                                 const cuuint32_t*, CUtensorMapInterleave, CUtensorMapSwizzle, CUtensorMapL2promotion, CUtensorMapFloatOOBfill);
    static bool init = false;
    static EncodeFn encode = nullptr;
    static void* scratch = nullptr;
    if (!init) {
        cudaFuncSetAttribute(mpnn_kernel, cudaFuncAttributeMaxDynamicSharedMemorySize, SMEM_BYTES);
        void* fn = nullptr;
        cudaDriverEntryPointQueryResult st;
        if (cudaGetDriverEntryPoint("cuTensorMapEncodeTiled", &fn, cudaEnableDefault, &st) == cudaSuccess && st == cudaDriverEntryPointSuccess) encode = (EncodeFn)fn;
        if (cudaGetSymbolAddress(&scratch, g_scratch) != cudaSuccess) scratch = nullptr;
        init = true;
    }
    CUtensorMap map = {};
    const cuuint64_t dims[2] = {128, 144}, strides[1] = {256};
    const cuuint32_t box[2] = {64, 16}, estr[2] = {1, 1};
    const bool have_map = encode && encode(&map, CU_TENSOR_MAP_DATA_TYPE_BFLOAT16, 2, d_in[4], dims, strides, box, estr, CU_TENSOR_MAP_INTERLEAVE_NONE,
                                          CU_TENSOR_MAP_SWIZZLE_128B, CU_TENSOR_MAP_L2_PROMOTION_NONE, CU_TENSOR_MAP_FLOAT_OOB_FILL_NONE) == CUDA_SUCCESS;
    mpnn_kernel<<<NCTA, NT, SMEM_BYTES>>>((const __nv_bfloat16*)d_in[0], (const __nv_bfloat16*)d_in[1], (const int*)d_in[2], (const int*)d_in[3],
                                          (const __nv_bfloat16*)d_in[4], (const __nv_bfloat16*)d_in[5], (const __nv_bfloat16*)d_in[6],
                                          (const __nv_bfloat16*)d_in[7], (__nv_bfloat16*)d_out, have_map ? (Scratch*)scratch : nullptr, map);
}
```

```cpp
#include <cuda_runtime.h>
#include <cuda.h>
#include <cuda_bf16.h>
#include <cuda_fp16.h>
#include <stdint.h>

namespace {

constexpr int N_NODES = 25000;
constexpr int N_EDGES = 800000;
constexpr int NCTA = 132;
constexpr int NPC = 190;
constexpr int NT = 640;
constexpr int NP = 512;
constexpr int CHUNK = 6060;
constexpr int R = 8;
#define SFP 3
#define WP 1
constexpr int CB = 352;
constexpr int MINB = 127;
constexpr int CAP = 91;
constexpr int SPITCH = 368;
constexpr int GPITCH = 24;
constexpr uint32_t TAGMOD = (1u << 22) - 1;
constexpr uint32_t EMPTY = 0xff000000u;
constexpr int SPIN = 1 << 16;
#define MBSPIN (1 << 22)

constexpr uint32_t SB = 1024;
constexpr uint32_t A_XR = SB;
constexpr uint32_t A_ER = A_XR + R * 8192;
constexpr uint32_t A_SEL = A_ER + R * 2048;
constexpr uint32_t QP = 200 * 128;
constexpr uint32_t A_QH = A_SEL + R * 2048;
constexpr uint32_t A_BIN = A_QH + 2 * QP;
constexpr uint32_t BIN1 = 0xa00, DUMP = BIN1 + 23 * CB * 4;
constexpr uint32_t A_CNT = A_BIN + DUMP + 16;
constexpr uint32_t A_BC = A_CNT + 136 * 4;
constexpr uint32_t A_DEG = A_BC + 32 * 4;
constexpr uint32_t A_EV = A_DEG + 256 * 4;
constexpr uint32_t A_MISC = A_EV + 256;
constexpr uint32_t A_ZEND = A_MISC + 16;
constexpr uint32_t A_TAG = A_ZEND;
constexpr uint32_t A_B1 = A_TAG + 16;
constexpr uint32_t A_B2 = A_B1 + 256;
constexpr uint32_t A_BAR = A_B2 + 128;
constexpr uint32_t A_SS = A_BAR + 18 * 8;
constexpr uint32_t A_END = A_SS + 4 * 512;
constexpr int SMEM_BYTES = A_END - SB;
constexpr uint32_t A_STG = A_XR;
constexpr uint32_t A_WB = A_SEL;
constexpr uint32_t A_WA = A_XR + 49 * 1024;
constexpr uint32_t A_XO = A_QH + QP;
constexpr uint32_t A_W2 = A_BIN;
constexpr uint32_t A_OUT = A_XR;
static_assert(A_STG + (NCTA + 1) * SPITCH + 16 <= A_WA && A_WA + 2 * 10240 <= A_SEL && CB * 4 + 1024 <= BIN1 && DUMP % 16 == 0 && 24 * CB / 128 < 128, "alias");
static_assert(A_QH % 1024 == 0 && QP % 1024 == 0 && A_WA % 1024 == 0 && A_SEL % 1024 == 0, "align");
static_assert(A_CNT % 16 == 0 && A_ZEND % 16 == 0 && A_B2 % 16 == 0 && A_B1 % 16 == 0 && A_BAR % 8 == 0 && A_BC % 16 == 0 && A_DEG % 8 == 0 && A_MISC % 16 == 0 && A_SS % 16 == 0, "align");
static_assert(SMEM_BYTES <= 199680 && A_ZEND - A_CNT <= 2048, "smem");

struct Scratch {
    uint4 flag[NCTA * 40];
    uint32_t cnt, pad[31];
    uint4 x16[N_NODES * 8];
    uint4 ent[NCTA * NCTA * GPITCH];
};
__device__ __align__(128) Scratch g_scratch;

#define TL(i)
#define TC(i)
#define TV(i, v)
#define TS(i)
#define TW(i)
#define TWD(i, v)
#define TSX(i, cond)

__device__ __forceinline__ void wg_fence() { asm volatile("wgmma.fence.sync.aligned;" ::: "memory"); }
__device__ __forceinline__ void wg_commit() { asm volatile("wgmma.commit_group.sync.aligned;" ::: "memory"); }
__device__ __forceinline__ void wg_wait0() { asm volatile("wgmma.wait_group.sync.aligned 0;" ::: "memory"); }
__device__ __forceinline__ void wg_wait1() { asm volatile("wgmma.wait_group.sync.aligned 1;" ::: "memory"); }
template <int M> __device__ __forceinline__ void fence_regs(uint32_t (&d)[M]) {
#pragma unroll
    for (int i = 0; i < M; i++) asm volatile("" : "+r"(d[i])::"memory");
}
template <int M> __device__ __forceinline__ void fence_regs(float (&d)[M]) {
#pragma unroll
    for (int i = 0; i < M; i++) asm volatile("" : "+f"(d[i])::"memory");
}
constexpr uint32_t HI128 = 0x40000040;
constexpr uint32_t HI32 = 0xC0000010;
template <int SC, uint32_t HI>
__device__ __forceinline__ void mma64h(uint32_t (&d)[16], const uint32_t (&a)[4], uint32_t lo) {
    asm volatile("{\n.reg .pred p;\n.reg .b64 dsc;\nsetp.ne.b32 p, %21, 0;\nmov.b64 dsc, {%20, %22};\n"
        "wgmma.mma_async.sync.aligned.m64n64k16.f16.f16.f16 {%0, %1, %2, %3, %4, %5, %6, %7, %8, %9, %10, %11, %12, %13, %14, %15}, {%16, %17, %18, %19}, dsc, p, 1, 1, 0;\n}\n"
        : "+r"(d[0]), "+r"(d[1]), "+r"(d[2]), "+r"(d[3]), "+r"(d[4]), "+r"(d[5]), "+r"(d[6]), "+r"(d[7]), "+r"(d[8]), "+r"(d[9]), "+r"(d[10]), "+r"(d[11]), "+r"(d[12]), "+r"(d[13]), "+r"(d[14]), "+r"(d[15])
        : "r"(a[0]), "r"(a[1]), "r"(a[2]), "r"(a[3]), "r"(lo), "n"(SC), "n"(HI));
}
template <uint32_t HI>
__device__ __forceinline__ void mma64h0(uint32_t (&d)[16], const uint32_t (&a)[4], uint32_t lo) {
    asm volatile("{\n.reg .pred p;\n.reg .b64 dsc;\nsetp.ne.b32 p, 0, 0;\nmov.b64 dsc, {%20, %21};\n"
        "wgmma.mma_async.sync.aligned.m64n64k16.f16.f16.f16 {%0, %1, %2, %3, %4, %5, %6, %7, %8, %9, %10, %11, %12, %13, %14, %15}, {%16, %17, %18, %19}, dsc, p, 1, 1, 0;\n}\n"
        : "=r"(d[0]), "=r"(d[1]), "=r"(d[2]), "=r"(d[3]), "=r"(d[4]), "=r"(d[5]), "=r"(d[6]), "=r"(d[7]), "=r"(d[8]), "=r"(d[9]), "=r"(d[10]), "=r"(d[11]), "=r"(d[12]), "=r"(d[13]), "=r"(d[14]), "=r"(d[15])
        : "r"(a[0]), "r"(a[1]), "r"(a[2]), "r"(a[3]), "r"(lo), "n"(HI));
}
template <uint32_t HI>
__device__ __forceinline__ void mma16t(uint32_t (&d)[4], uint32_t a0, uint32_t a1, uint32_t a2, uint32_t a3, uint32_t lo) {
    asm volatile("{\n.reg .pred p;\n.reg .b64 dsc;\nsetp.eq.b32 p, 0, 0;\nmov.b64 dsc, {%8, %9};\n"
        "wgmma.mma_async.sync.aligned.m64n16k16.f16.f16.f16 {%0, %1, %2, %3}, {%4, %5, %6, %7}, dsc, p, 1, 1, 1;\n}\n"
        : "+r"(d[0]), "+r"(d[1]), "+r"(d[2]), "+r"(d[3]) : "r"(a0), "r"(a1), "r"(a2), "r"(a3), "r"(lo), "n"(HI));
}
template <int SC, uint32_t HI>
__device__ __forceinline__ void mma96h(uint32_t (&d)[24], const uint32_t (&a)[4], uint32_t lo) {
    asm volatile("{\n.reg .pred p;\n.reg .b64 dsc;\nsetp.ne.b32 p, %29, 0;\nmov.b64 dsc, {%28, %30};\n"
        "wgmma.mma_async.sync.aligned.m64n96k16.f16.f16.f16 {%0, %1, %2, %3, %4, %5, %6, %7, %8, %9, %10, %11, %12, %13, %14, %15, %16, %17, %18, %19, %20, %21, %22, %23}, {%24, %25, %26, %27}, dsc, p, 1, 1, 0;\n}\n"
        : "+r"(d[0]), "+r"(d[1]), "+r"(d[2]), "+r"(d[3]), "+r"(d[4]), "+r"(d[5]), "+r"(d[6]), "+r"(d[7]), "+r"(d[8]), "+r"(d[9]), "+r"(d[10]), "+r"(d[11]), "+r"(d[12]), "+r"(d[13]), "+r"(d[14]), "+r"(d[15]), "+r"(d[16]), "+r"(d[17]), "+r"(d[18]), "+r"(d[19]), "+r"(d[20]), "+r"(d[21]), "+r"(d[22]), "+r"(d[23])
        : "r"(a[0]), "r"(a[1]), "r"(a[2]), "r"(a[3]), "r"(lo), "n"(SC), "n"(HI));
}
template <int SC, uint32_t HI>
__device__ __forceinline__ void mma48f(float (&d)[24], const uint32_t (&a)[4], uint32_t lo) {
    asm volatile("{\n.reg .pred p;\n.reg .b64 dsc;\nsetp.ne.b32 p, %29, 0;\nmov.b64 dsc, {%28, %30};\n"
        "wgmma.mma_async.sync.aligned.m64n48k16.f32.f16.f16 {%0, %1, %2, %3, %4, %5, %6, %7, %8, %9, %10, %11, %12, %13, %14, %15, %16, %17, %18, %19, %20, %21, %22, %23}, {%24, %25, %26, %27}, dsc, p, 1, 1, 0;\n}\n"
        : "+f"(d[0]), "+f"(d[1]), "+f"(d[2]), "+f"(d[3]), "+f"(d[4]), "+f"(d[5]), "+f"(d[6]), "+f"(d[7]), "+f"(d[8]), "+f"(d[9]), "+f"(d[10]), "+f"(d[11]), "+f"(d[12]), "+f"(d[13]), "+f"(d[14]), "+f"(d[15]), "+f"(d[16]), "+f"(d[17]), "+f"(d[18]), "+f"(d[19]), "+f"(d[20]), "+f"(d[21]), "+f"(d[22]), "+f"(d[23])
        : "r"(a[0]), "r"(a[1]), "r"(a[2]), "r"(a[3]), "r"(lo), "n"(SC), "n"(HI));
}
__device__ __forceinline__ uint32_t hadd2(uint32_t a, uint32_t b) { uint32_t r; asm("add.rn.f16x2 %0, %1, %2;" : "=r"(r) : "r"(a), "r"(b)); return r; }
__device__ __forceinline__ uint32_t hfma2(uint32_t a, uint32_t b, uint32_t c) { uint32_t r; asm("fma.rn.f16x2 %0, %1, %2, %3;" : "=r"(r) : "r"(a), "r"(b), "r"(c)); return r; }
__device__ __forceinline__ uint32_t htanh2(uint32_t a) { uint32_t r; asm("tanh.approx.f16x2 %0, %1;" : "=r"(r) : "r"(a)); return r; }
__device__ __forceinline__ uint32_t pack_h2(float lo, float hi) { uint32_t r; asm("cvt.rn.f16x2.f32 %0, %1, %2;" : "=r"(r) : "f"(hi), "f"(lo)); return r; }
__device__ __forceinline__ uint32_t pack_b2(float lo, float hi) { uint32_t r; asm("cvt.rn.bf16x2.f32 %0, %1, %2;" : "=r"(r) : "f"(hi), "f"(lo)); return r; }
__device__ __forceinline__ uint32_t bf2h(uint32_t v) { return pack_h2(__uint_as_float(v << 16), __uint_as_float(v & 0xffff0000u)); }
__device__ __forceinline__ uint32_t bf2h_half(uint32_t v) { return pack_h2(0.5f * __uint_as_float(v << 16), 0.5f * __uint_as_float(v & 0xffff0000u)); }
__device__ __forceinline__ uint4 bf2h4(uint4 v) { return make_uint4(bf2h(v.x), bf2h(v.y), bf2h(v.z), bf2h(v.w)); }

__device__ __forceinline__ void cp16(uint32_t s, const void* g) { asm volatile("cp.async.cg.shared.global [%0], [%1], 16;" ::"r"(s), "l"(g) : "memory"); }
__device__ __forceinline__ void cp_commit() { asm volatile("cp.async.commit_group;" ::: "memory"); }
template <int N> __device__ __forceinline__ void cp_wait() { asm volatile("cp.async.wait_group %0;" ::"n"(N) : "memory"); }
__device__ __forceinline__ void bulk_g2s(uint32_t s, const void* g, uint32_t bytes, uint32_t bar) {
    asm volatile("cp.async.bulk.shared::cluster.global.mbarrier::complete_tx::bytes [%0], [%1], %2, [%3];" ::"r"(s), "l"(g), "r"(bytes), "r"(bar) : "memory");
}
__device__ __forceinline__ void tma_g2s(uint32_t s, const CUtensorMap* m, int c0, int c1, uint32_t bar) {
    asm volatile("cp.async.bulk.tensor.2d.shared::cluster.global.mbarrier::complete_tx::bytes [%0], [%1, {%2, %3}], [%4];" ::"r"(s), "l"(m), "r"(c0), "r"(c1), "r"(bar) : "memory");
}
__device__ __forceinline__ void l2_prefetch(const void* g, uint32_t bytes) { asm volatile("cp.async.bulk.prefetch.L2.global [%0], %1;" ::"l"(g), "r"(bytes) : "memory"); }
__device__ __forceinline__ void proxy_fence() { asm volatile("fence.proxy.async.shared::cta;" ::: "memory"); }
__device__ __forceinline__ bool mbar_try(uint32_t bar, uint32_t parity) {
    uint32_t ok;
    asm volatile("{\n.reg .pred p;\nmbarrier.try_wait.parity.shared::cta.b64 p, [%1], %2;\nselp.u32 %0, 1, 0, p;\n}" : "=r"(ok) : "r"(bar), "r"(parity) : "memory");
    return ok;
}
__device__ __forceinline__ void mbar_wait(uint32_t bar, uint32_t parity) {
    if (__builtin_expect(!mbar_try(bar, parity), 0))
        for (int it = 0; it < MBSPIN; it++) if (mbar_try(bar, parity)) break;
}
__device__ __forceinline__ void mbar_arrive(uint32_t bar) { asm volatile("mbarrier.arrive.shared::cta.b64 _, [%0];" ::"r"(bar) : "memory"); }
__device__ __forceinline__ uint32_t lds32(uint32_t a) { uint32_t r; asm volatile("ld.shared.u32 %0, [%1];" : "=r"(r) : "r"(a) : "memory"); return r; }
__device__ __forceinline__ uint32_t lds16(uint32_t a) { uint32_t r; asm volatile("ld.shared.u16 %0, [%1];" : "=r"(r) : "r"(a) : "memory"); return r; }
__device__ __forceinline__ uint2 lds64(uint32_t a) { uint2 r; asm volatile("ld.shared.v2.u32 {%0,%1}, [%2];" : "=r"(r.x), "=r"(r.y) : "r"(a) : "memory"); return r; }
__device__ __forceinline__ uint4 lds128(uint32_t a) { uint4 r; asm volatile("ld.shared.v4.u32 {%0,%1,%2,%3}, [%4];" : "=r"(r.x), "=r"(r.y), "=r"(r.z), "=r"(r.w) : "r"(a) : "memory"); return r; }
__device__ __forceinline__ void sts128(uint32_t a, uint4 v) { asm volatile("st.shared.v4.u32 [%0], {%1,%2,%3,%4};" ::"r"(a), "r"(v.x), "r"(v.y), "r"(v.z), "r"(v.w) : "memory"); }
__device__ __forceinline__ void sts64(uint32_t a, uint32_t x, uint32_t y) { asm volatile("st.shared.v2.u32 [%0], {%1,%2};" ::"r"(a), "r"(x), "r"(y) : "memory"); }
__device__ __forceinline__ void sts32(uint32_t a, uint32_t v) { asm volatile("st.shared.u32 [%0], %1;" ::"r"(a), "r"(v) : "memory"); }
__device__ __forceinline__ void sts16(uint32_t a, uint32_t v) { asm volatile("st.shared.u16 [%0], %1;" ::"r"(a), "r"(v) : "memory"); }
__device__ __forceinline__ void sts8(uint32_t a, uint32_t v) { asm volatile("st.shared.u8 [%0], %1;" ::"r"(a), "r"(v) : "memory"); }
__device__ __forceinline__ void sts32_z(uint32_t a, uint32_t v, uint32_t z) {
    asm volatile("{\n.reg .pred p;\nsetp.eq.u32 p, %2, 0;\n@p st.shared.u32 [%0], %1;\n}" ::"r"(a), "r"(v), "r"(z) : "memory");
}
__device__ __forceinline__ uint32_t atoms_inc(uint32_t a) { uint32_t r; asm volatile("atom.shared.add.u32 %0, [%1], 1;" : "=r"(r) : "r"(a) : "memory"); return r; }
__device__ __forceinline__ uint32_t bin_slot(uint32_t e) {
    uint32_t r;
    asm volatile("atom.shared.add.u32 %0, [%1], 4;" : "=r"(r) : "r"(A_BC + ((e >> 1) & 0x7c)) : "memory");
    return r;
}
__device__ __forceinline__ uint32_t bin_base(int b, int nb) { return b == 0 ? 0u : b == nb - 1 ? BIN1 : BIN1 + b * CB * 4; }
__device__ __forceinline__ void deg_inc(uint32_t v) { asm volatile("red.shared.add.u32 [%0], 1;" ::"r"(A_DEG + (v >> 22)) : "memory"); }
__device__ __forceinline__ uint32_t ldg_rlx32(const void* p) { uint32_t r; asm volatile("ld.relaxed.gpu.global.u32 %0, [%1];" : "=r"(r) : "l"(p) : "memory"); return r; }
#define LDI "ld.relaxed.gpu.global.v2.u32"
__device__ __forceinline__ int2 ldg64(const void* p) { int2 r; asm volatile(LDI " {%0,%1}, [%2];" : "=r"(r.x), "=r"(r.y) : "l"(p) : "memory"); return r; }
__device__ __forceinline__ void ldg64_if(int2& r, const void* p, bool on) {
    asm volatile("{\n.reg .pred p;\nsetp.ne.u32 p, %3, 0;\n@p " LDI " {%0,%1}, [%2];\n}" : "+r"(r.x), "+r"(r.y) : "l"(p), "r"((uint32_t)on) : "memory");
}
__device__ __forceinline__ uint4 ldg_rlx128_if(const void* p, bool on) {
    uint4 r;
    asm volatile("{\n.reg .pred p;\n.reg .b64 a, b;\nsetp.ne.u32 p, %5, 0;\n@p ld.relaxed.gpu.global.v2.b64 {a, b}, [%4];\nmov.b64 {%0,%1}, a;\nmov.b64 {%2,%3}, b;\n}"
                 : "=r"(r.x), "=r"(r.y), "=r"(r.z), "=r"(r.w) : "l"(p), "r"((uint32_t)on) : "memory");
    return r;
}
__device__ __forceinline__ void ldg_rlx128_upd(uint64_t& a, uint64_t& b, const void* p, bool on) {
    asm volatile("{\n.reg .pred p;\nsetp.ne.u32 p, %3, 0;\n@p ld.relaxed.gpu.global.v2.b64 {%0, %1}, [%2];\n}" : "+l"(a), "+l"(b) : "l"(p), "r"((uint32_t)on) : "memory");
}
__device__ __forceinline__ uint2 ldg_rlx64_if(const void* p, bool on) {
    uint64_t a = 0;
    asm volatile("{\n.reg .pred p;\nsetp.ne.u32 p, %2, 0;\n@p ld.relaxed.gpu.global.b64 %0, [%1];\n}" : "+l"(a) : "l"(p), "r"((uint32_t)on) : "memory");
    return make_uint2((uint32_t)a, (uint32_t)(a >> 32));
}
__device__ __forceinline__ uint4 ldg_acq128(const void* p) {
    uint4 r;
    asm volatile("ld.acquire.gpu.global.v4.u32 {%0,%1,%2,%3}, [%4];" : "=r"(r.x), "=r"(r.y), "=r"(r.z), "=r"(r.w) : "l"(p) : "memory");
    return r;
}
__device__ __forceinline__ void stg_rlx32(void* p, uint32_t v) { asm volatile("st.relaxed.gpu.global.u32 [%0], %1;" ::"l"(p), "r"(v) : "memory"); }
__device__ __forceinline__ void stg_rlx128(void* p, uint4 v) {
    asm volatile("{\n.reg .b64 a, b;\nmov.b64 a, {%1,%2};\nmov.b64 b, {%3,%4};\nst.relaxed.gpu.global.v2.b64 [%0], {a, b};\n}" ::"l"(p), "r"(v.x), "r"(v.y), "r"(v.z), "r"(v.w) : "memory");
}
__device__ __forceinline__ void stg_rlx128_if(void* p, uint4 v, bool on) {
    asm volatile("{\n.reg .pred p;\n.reg .b64 a, b;\nsetp.ne.u32 p, %5, 0;\nmov.b64 a, {%1,%2};\nmov.b64 b, {%3,%4};\n@p st.relaxed.gpu.global.v2.b64 [%0], {a, b};\n}" ::"l"(p), "r"(v.x), "r"(v.y), "r"(v.z), "r"(v.w), "r"((uint32_t)on) : "memory");
}
__device__ __forceinline__ void ldsm4t(uint32_t (&r)[4], uint32_t a) {
    asm volatile("ldmatrix.sync.aligned.m8n8.x4.trans.shared.b16 {%0,%1,%2,%3}, [%4];" : "=r"(r[0]), "=r"(r[1]), "=r"(r[2]), "=r"(r[3]) : "r"(a) : "memory");
}
__device__ __forceinline__ void ldsm2t(uint32_t& r0, uint32_t& r1, uint32_t a) {
    asm volatile("ldmatrix.sync.aligned.m8n8.x2.trans.shared.b16 {%0,%1}, [%2];" : "=r"(r0), "=r"(r1) : "r"(a) : "memory");
}
__device__ __forceinline__ void stsm2t(uint32_t a, uint32_t r0, uint32_t r1) {
    asm volatile("stmatrix.sync.aligned.m8n8.x2.trans.shared.b16 [%0], {%1,%2};" ::"r"(a), "r"(r0), "r"(r1) : "memory");
}
__device__ __forceinline__ void stsm4t(uint32_t a, uint32_t r0, uint32_t r1, uint32_t r2, uint32_t r3) {
    asm volatile("stmatrix.sync.aligned.m8n8.x4.trans.shared.b16 [%0], {%1,%2,%3,%4};" ::"r"(a), "r"(r0), "r"(r1), "r"(r2), "r"(r3) : "memory");
}
template <int ID, int N> __device__ __forceinline__ void bar_sync() { asm volatile("bar.sync %0, %1;" ::"n"(ID), "n"(N) : "memory"); }
template <int ID, int N> __device__ __forceinline__ void bar_arrive() { asm volatile("bar.arrive %0, %1;" ::"n"(ID), "n"(N) : "memory"); }
__device__ __forceinline__ uint32_t scan_up(uint32_t v) {
#pragma unroll
    for (int o = 1; o < 32; o <<= 1)
        asm volatile("{\n.reg .pred p;\n.reg .u32 t;\nshfl.sync.up.b32 t|p, %0, %1, 0, -1;\n@p add.u32 %0, %0, t;\n}" : "+r"(v) : "r"(o));
    return v;
}
__device__ __forceinline__ float bf2f(const __nv_bfloat16* p) { return __bfloat162float(*p); }

__device__ __forceinline__ int chunk_start(int c) { return c * CHUNK + min(c, 40) * 2; }
static_assert(NCTA * CHUNK + 80 == N_EDGES && CHUNK / 2 + 1 <= 6 * NP && CHUNK / 2 >= 5 * NP, "chunks");

struct Sched { uint32_t len, start, total; int L, L1, B0; bool fail; };
__device__ __forceinline__ Sched schedule(int lane, int nb) {
    Sched r;
    const uint32_t n = (lds32(A_BC + lane * 4) - bin_base(lane, nb)) >> 2, f = lds32(A_MISC);
    r.len = lane < nb ? max(n, (uint32_t)MINB) : 0u;
    const uint32_t end = scan_up(r.len);
    r.start = end - r.len;
    r.total = __shfl_sync(0xffffffffu, end, 31);
    r.L = (r.total + 127) >> 7;
    r.L1 = ((r.total + 63) >> 6) - r.L;
    r.B0 = __popc(__ballot_sync(0xffffffffu, end <= 64u * r.L));
    r.fail = __any_sync(0xffffffffu, r.len > CB || f);
    return r;
}
static_assert(64 * ((14 * MINB + 127) / 128) >= 2 * CB && 14 * MINB / 2 - 64 > 2 * CB, "block B0 is never among the first two of a stream");

__device__ __noinline__ void slow_path(uint8_t* sp, const __nv_bfloat16* x, const __nv_bfloat16* ea, const int* src, const int* dst,
                                       const __nv_bfloat16* w1, const __nv_bfloat16* b1, const __nv_bfloat16* w2,
                                       const __nv_bfloat16* b2, __nv_bfloat16* out) {
    const int tid = threadIdx.x, lane = tid & 31, warp = tid >> 5, cta = blockIdx.x;
    const int nrows = min(NPC, N_NODES - cta * NPC);
    float* hs = (float*)sp;
    __nv_bfloat16* w1s = (__nv_bfloat16*)(sp + 192 * 128 * 4);
    int* dg = (int*)(sp + 192 * 128 * 4 + 144 * 128 * 2);
    __syncthreads();
    for (int i = tid; i < 192 * 128; i += NT) hs[i] = 0.f;
    for (int i = tid; i < 144 * 128; i += NT) w1s[i] = w1[i];
    for (int i = tid; i < 192; i += NT) dg[i] = 0;
    __syncthreads();
    float bb[4];
    for (int j = 0; j < 4; j++) bb[j] = bf2f(b1 + lane * 4 + j);
    for (int i0 = warp * 32; i0 < N_EDGES; i0 += NT) {
        const int mine = dst[i0 + lane] - cta * NPC;
        uint32_t hit = __ballot_sync(0xffffffffu, (unsigned)mine < (unsigned)nrows);
        while (hit) {
            const int b = __ffs(hit) - 1;
            hit &= hit - 1;
            const int eid = i0 + b, dl = __shfl_sync(0xffffffffu, mine, b), s = src[eid];
            float v[5];
            v[0] = bf2f(x + s * 64 + lane); v[1] = bf2f(x + s * 64 + 32 + lane);
            v[2] = bf2f(x + (cta * NPC + dl) * 64 + lane); v[3] = bf2f(x + (cta * NPC + dl) * 64 + 32 + lane);
            v[4] = lane < 16 ? bf2f(ea + (size_t)eid * 16 + lane) : 0.f;
            float z[4] = {bb[0], bb[1], bb[2], bb[3]};
#pragma unroll
            for (int c = 0; c < 5; c++) {
                for (int kk = 0; kk < (c == 4 ? 16 : 32); kk++) {
                    float a = __shfl_sync(0xffffffffu, v[c], kk);
                    const __nv_bfloat16* wr = w1s + (c * 32 + kk) * 128 + lane * 4;
#pragma unroll
                    for (int j = 0; j < 4; j++) z[j] = fmaf(a, __bfloat162float(wr[j]), z[j]);
                }
            }
#pragma unroll
            for (int j = 0; j < 4; j++) atomicAdd(&hs[dl * 128 + lane * 4 + j], z[j] / (1.f + expf(-z[j])));
            if (lane == 0) atomicAdd(&dg[dl], 1);
        }
    }
    __syncthreads();
    for (int i = tid; i < nrows * 64; i += NT) {
        int n = i >> 6, d = i & 63;
        float a = 0.f;
        if (dg[n] > 0) {
            a = (float)dg[n] * bf2f(b2 + d);
            for (int h = 0; h < 128; h++) a = fmaf(hs[n * 128 + h], bf2f(w2 + h * 64 + d), a);
        }
        out[(size_t)(cta * NPC + n) * 64 + d] = __float2bfloat16(a);
    }
}

__global__ void __launch_bounds__(NT, 1)
mpnn_kernel(const __nv_bfloat16* __restrict__ x, const __nv_bfloat16* __restrict__ ea, const int* __restrict__ src,
            const int* __restrict__ dst, const __nv_bfloat16* __restrict__ w1, const __nv_bfloat16* __restrict__ b1,
            const __nv_bfloat16* __restrict__ w2, const __nv_bfloat16* __restrict__ b2, __nv_bfloat16* __restrict__ out,
            Scratch* __restrict__ gs, const __grid_constant__ CUtensorMap w1map) {
    extern __shared__ uint8_t smem_raw[];
    const int tid = threadIdx.x, lane = tid & 31;
    __builtin_assume(tid < NT);
    const int warp = __shfl_sync(0xffffffffu, tid >> 5, 0);
    const int cta = blockIdx.x;
    const int nrows = min(NPC, N_NODES - cta * NPC), nb = (nrows + 7) >> 3;
    const int e0 = chunk_start(cta);
    const int nv2 = CHUNK / 2 + (cta < 40);
    if ((uint32_t)__cvta_generic_to_shared(smem_raw) != SB || !gs) { slow_path(smem_raw, x, ea, src, dst, w1, b1, w2, b2, out); return; }
    constexpr uint32_t bar_w = A_BAR + R * 16, bar_x = bar_w + 8;
    const int wg = warp >> 2, wq = warp & 3, hh = wg & 1, strm = wg >> 1;
    const uint32_t qch = wq * 2 + ((lane >> 3) & 1);
    const uint32_t wofs = (((lane >> 4) & 1) * 8 + (lane & 7)) * 128 + ((qch ^ (lane & 7)) << 4);
    int bad = 0;
    TS(0);

    int2 d2[6];
    const int pt = tid - NP;
    if (wg == 4) {
        uint32_t cnt0;
        if (pt == 64) cnt0 = ldg_rlx32(&gs->cnt);
        if (pt == 96) {
#pragma unroll
            for (int i = 0; i < 2 * R + 2; i++) asm volatile("mbarrier.init.shared::cta.b64 [%0], %1;" ::"r"(A_BAR + i * 8), "r"(i < R ? 2 : i < 2 * R ? 8 : 1) : "memory");
            proxy_fence();
            asm volatile("mbarrier.arrive.expect_tx.shared::cta.b64 _, [%0], %1;" ::"r"(bar_w), "r"(144 * 256 + 256 + 128) : "memory");
            asm volatile("mbarrier.arrive.expect_tx.shared::cta.b64 _, [%0], %1;" ::"r"(bar_x), "r"(nrows * 128) : "memory");
        }
        __syncwarp();
        if (pt < (int)(A_ZEND - A_CNT) / 16) sts128(A_CNT + pt * 16, make_uint4(0, 0, 0, 0));
        if (pt == 64) {
            const uint32_t tag = cnt0 / NCTA + 1;
            sts64(A_TAG, tag << 21, tag >> 11 << 21);
        }
    } else {
        const int2* dp = (const int2*)(dst + e0) + tid;
        d2[5] = make_int2(NCTA * NPC, NCTA * NPC);
#pragma unroll
        for (int r = 0; r < 5; r++) d2[r] = ldg64(dp + r * NP);
        ldg64_if(d2[5], dp + 5 * NP, tid < nv2 - 5 * NP);
        stg_rlx128_if(gs->ent + ((tid >> 1) * NCTA + cta) * GPITCH + (lane & 1), make_uint4(0, 0, 0, 0), tid < 2 * NCTA);
    }
    __syncthreads();
    const uint2 tag = lds64(A_TAG);
    if (wg == 4) {
        const uint32_t tagw = tag.x | tag.y >> 11;
        if (warp == 19) {
            if (lane == 0) {
                bulk_g2s(A_XO, x + cta * NPC * 64, nrows * 128, bar_x);
                asm volatile("red.relaxed.gpu.global.inc.u32 [%0], %1;" ::"l"(&gs->cnt), "r"(NCTA * TAGMOD - 1) : "memory");
            }
            TSX(15, lane == 0);
            __syncwarp();
            if (lane < 18) {
                int i = lane + cta % 18;
                i = i >= 18 ? i - 18 : i;
                const int h = i & 1, rb = i >> 1;
                tma_g2s(rb >= 4 && rb < 8 ? A_WB + h * 8192 + (rb - 4) * 2048 : A_WA + h * 10240 + min(rb, 4) * 2048, &w1map, h * 64, rb * 16, bar_w);
            } else if (lane < 20) bulk_g2s(lane == 18 ? A_B1 : A_B2, lane == 18 ? b1 : b2, lane == 18 ? 256 : 128, bar_w);
            else if (lane == 20) l2_prefetch(w2, 128 * 64 * 2);
            __syncwarp();
        }
        if (warp == 16) sts32(A_BC + lane * 4, lane < 24 ? bin_base(lane, nb) : DUMP);
#pragma unroll 1
        for (uint32_t a = A_BIN + pt * 16; a < A_BIN + DUMP; a += 2048) sts128(a, make_uint4(EMPTY, EMPTY, EMPTY, EMPTY));
        bar_arrive<1, NT>();
        mbar_wait(bar_x, 0);
        TW(0);
        const uint32_t xo = A_XO + (pt >> 3) * 128 + (((pt ^ (pt >> 3)) & 7) << 4);
        {
            uint4 xr[12];
#pragma unroll
            for (int r = 0; r < 12; r++) xr[r] = lds128(A_XO + (r * 128 + pt) * 16);
            __syncwarp();
#pragma unroll
            for (int r = 0; r < 12; r++) {
                const bool in = r * 128 + pt < nrows * 8;
                const uint4 v = in ? bf2h4(xr[r]) : make_uint4(0, 0, 0, 0);
                sts128(xo + r * 2048, v);
                if (in) gs->x16[cta * NPC * 8 + r * 128 + pt] = v;
            }
        }
        proxy_fence();
        mbar_wait(bar_w, 0);
        bar_sync<4, 128>();
        TW(1);
        if (warp == 19) {
            asm volatile("fence.acq_rel.gpu;" ::: "memory");
#pragma unroll
            for (int j = 0; j < 5; j++)
                if (j * 32 + lane < NCTA) stg_rlx32((uint32_t*)(gs->flag + (j * 32 + lane) * 40) + cta, tagw);
            TSX(16, lane == 0);
            __syncwarp();
        }
#pragma unroll 1
        for (int h = 0; h < 2; h++) {
            uint32_t wb[4][4], acc[2][24];
#pragma unroll
            for (int i = 0; i < 4; i++) ldsm4t(wb[i], A_WB + h * 8192 + wofs + i * 2048);
            const uint32_t bl0 = lds16(A_B1 + (h * 64 + wq * 16 + (lane >> 2)) * 2), bl1 = lds16(A_B1 + (h * 64 + wq * 16 + 8 + (lane >> 2)) * 2);
#pragma unroll
            for (int i = 0; i < 4; i++)
#pragma unroll
                for (int j = 0; j < 4; j++) wb[i][j] = bf2h_half(wb[i][j]);
            const uint32_t bq0 = bf2h_half(bl0 * 0x10001u), bq1 = bf2h_half(bl1 * 0x10001u);
#pragma unroll
            for (int i = 0; i < 4; i++) fence_regs(wb[i]);
            wg_fence();
#pragma unroll
            for (int n = 0; n < 2; n++) {
                const uint32_t lo = ((A_XO >> 4) | 0x10000) + n * 768;
                mma96h<0, HI128>(acc[n], wb[0], lo);
                mma96h<1, HI128>(acc[n], wb[1], lo + 2);
                mma96h<1, HI128>(acc[n], wb[2], lo + 4);
                mma96h<1, HI128>(acc[n], wb[3], lo + 6);
            }
            wg_commit();
            wg_wait0();
            fence_regs(acc[0]); fence_regs(acc[1]);
            if (h) {
                if (warp == 16) {
                    bool ok = false;
                    for (int it = 0; it < SPIN && !ok; it++) {
                        const uint4 f0 = ldg_acq128(gs->flag + cta * 40 + lane), f1 = ldg_acq128(gs->flag + cta * 40 + 32);
                        ok = __all_sync(0xffffffffu, f0.x == tagw && f0.y == tagw && f0.z == tagw && f0.w == tagw && f1.x == tagw && f1.y == tagw && f1.z == tagw && f1.w == tagw);
                    }
                    bad = !ok;
                    TSX(17, lane == 0);
                }
                bar_sync<4, 128>();
            }
#pragma unroll
            for (int n = 0; n < 2; n++)
#pragma unroll
                for (int j = 0; j < 6; j++)
                    stsm4t(A_QH + h * QP + n * 12288 + wofs + j * 2048, hadd2(acc[n][4 * j], bq0), hadd2(acc[n][4 * j + 1], bq1), hadd2(acc[n][4 * j + 2], bq0), hadd2(acc[n][4 * j + 3], bq1));
        }
        if (pt == 64) l2_prefetch(src + cta * 6064, min(6064, N_EDGES - cta * 6064) * 4);
        TW(2);
        const int par = wq >> 1, hf = wq & 1, gq = lane >> 3, cp = (lane >> 1) & 3;
        const uint32_t sel = A_SEL + hf * 2048 + (par * 32 + lane) * 32 + ((lane >> 2) & 1) * 16;
#pragma unroll
        for (int r = 0; r < 8; r++) sts128(A_SEL + hf * 2048 + par * 1024 + (r >> 1) * 4096 + (r & 1) * 512 + lane * 16, make_uint4(0, 0, 0, 0));
        const uint32_t bar_full = A_BAR + hf * 8, bar_empty = bar_full + R * 8;
        uint32_t xd[8];
#pragma unroll
        for (int c = 0; c < 8; c++) xd[c] = A_XR + hf * 8192 + (par * 32 + gq * 8) * 128 + (((lane & 7) ^ c) << 4);
        fence_regs(xd);
        uint32_t ed0 = A_ER + hf * 2048 + (par * 32 + gq * 8 + cp) * 32 + (lane & 1) * 16, ed1 = (ed0 ^ 16) + 128;
        const uint32_t sw = A_SS + wq * 128 + lane * 4, sr = A_SS + wq * 128 + gq * 32;
        const char* xg = (const char*)gs->x16 + (lane & 7) * 16;
        const char* eg = (const char*)ea + (lane & 1) * 16;
        const char* sp = (const char*)src;
        int bi = hf ? nb - 1 : 0;
        uint32_t ta = A_BIN + hf * BIN1 + (par * 32 + lane) * 4;
        asm volatile("" : "+l"(xg), "+l"(eg), "+l"(sp), "+r"(ed0), "+r"(ed1), "+r"(ta));
        uint32_t prev[4] = {sel, sel, sel, sel}, own[4], col[4];
        auto issue_e = [&](int st, uint32_t e) {
            const uint32_t e0 = __shfl_sync(0xffffffffu, e, gq * 8 + cp), e1 = __shfl_sync(0xffffffffu, e, gq * 8 + cp + 4);
            cp16(ed0 + st * 4096, eg + (size_t)(e0 & 0xfffff) * 32);
            cp16(ed1 + st * 4096, eg + (size_t)(e1 & 0xfffff) * 32);
            col[st] = e;
        };
        auto issue_x = [&](int st, const uint4& a0, const uint4& a1) {
            const uint32_t a[8] = {a0.x, a0.y, a0.z, a0.w, a1.x, a1.y, a1.z, a1.w};
#pragma unroll
            for (int i = 0; i < 8; i++) cp16(xd[i] + st * 16384 + i * 128, xg + (size_t)a[i] * 128);
        };
        auto fetch_src = [&](int slot, uint32_t e) {
            asm volatile("cp.async.ca.shared.global [%0], [%1], 4;" ::"r"(sw + slot * 512), "l"(sp + (size_t)(e & 0xfffff) * 4) : "memory");
        };
        auto finish = [&](int u) {
            const uint4 v0 = lds128(ed0 + u * 4096), v1 = lds128(ed1 + u * 4096);
            sts16(prev[u] + u * 4096, 0);
            prev[u] = sel ^ ((col[u] >> 23) & 0x1e);
            sts16(prev[u] + u * 4096, col[u] < (192u << 24) ? 0x3c00 : 0);
            sts128(ed0 + u * 4096, bf2h4(v0));
            sts128(ed1 + u * 4096, bf2h4(v1));
            proxy_fence();
            __syncwarp();
            if (lane == 0) mbar_arrive(bar_full + u * 16);
        };
        bar_sync<12, NT>();
        TSX(9, tid == 512);
        own[0] = lds32(ta);
        fetch_src(0, own[0]);
        cp_commit();
        issue_e(0, own[0]);
        cp_commit();
        const Sched sc = schedule(lane, nb);
        bar_sync<5, NT>();
        TW(3);
        if (!sc.fail) {
            const int L = hf ? sc.L1 : sc.L, dir = hf ? -1 : 1;
            uint32_t bs = A_BIN + bin_base(lane, nb), be = bs + sc.len * 4;
            if (lane == sc.B0) { const uint32_t cut = bs + (64 * sc.L - sc.start) * 4; if (hf) bs = cut; else be = cut; }
            if (lane == sc.B0 + dir) { bs = A_BIN + CB * 4; be = ~0u; }
            uint32_t nx = __shfl_sync(0xffffffffu, be, bi);
            auto next_entry = [&]() {
                ta += 256;
                while (__builtin_expect(__any_sync(0xffffffffu, ta >= nx), 0)) {
                    const bool c = ta >= nx;
                    if (c) bi += dir;
                    const uint32_t s2 = __shfl_sync(0xffffffffu, bs, bi), e2 = __shfl_sync(0xffffffffu, be, bi);
                    if (c) { ta += s2 - nx; nx = e2; }
                }
                return lds32(ta);
            };
            {
                own[1] = next_entry();
                own[2] = next_entry();
                fetch_src(1, own[1]);
                fetch_src(2, own[2]);
                cp_commit();
                own[3] = next_entry();
                own[0] = next_entry();
                const uint32_t o5 = next_entry();
                cp_wait<2>();
                __syncwarp();
                issue_x(0, lds128(sr), lds128(sr + 16));
                fetch_src(3, own[3]);
                cp_commit();
                TW(4);
                cp_wait<1>();
                __syncwarp();
#pragma unroll
                for (int t = 1; t < 3; t++) {
                    const uint4 a0 = lds128(sr + t * 512), a1 = lds128(sr + t * 512 + 16);
                    issue_e(t, own[t]);
                    issue_x(t, a0, a1);
                    fetch_src(t - 1, t == 1 ? own[0] : o5);
                    cp_commit();
                }
                own[1] = o5;
            }
            cp_wait<2>();
            TW(5);
            finish(0);
            TW(6);
            uint32_t ph = 1;
            for (int j = L;; j -= 4) {
#pragma unroll
                for (int u = 1; u < 5; u++) {
                    if (j == u) goto done;
                    if (u == 2) ph ^= 1;
                    const int st = (u + 2) & 3;
                    if (j > u + 2) {
                        const uint32_t es = next_entry();
                        const uint4 a0 = lds128(sr + st * 512), a1 = lds128(sr + st * 512 + 16);
                        fetch_src((st + 3) & 3, es);
                        mbar_wait(bar_empty + st * 16, ph);
                        issue_e(st, own[st]);
                        issue_x(st, a0, a1);
                        own[(st + 3) & 3] = es;
                    } else mbar_wait(bar_empty + st * 16, ph);
                    cp_commit();
                    cp_wait<2>();
                    finish(u & 3);
                }
            }
        done:
            if (lane == 0) mbar_arrive(bar_full + (L & 3) * 16);
            TSX(18, tid == 512);
            uint4 v[8];
#pragma unroll
            for (int i = 0; i < 8; i++) v[i] = __ldg((const uint4*)w2 + i * 128 + pt);
            bar_sync<4, 128>();
#pragma unroll
            for (int i = 0; i < 8; i++) sts128(A_W2 + (i * 16 + (pt >> 3)) * 144 + (pt & 7) * 16, bf2h4(v[i]));
            bar_arrive<3, NT>();
        } else bad = 1;
        cp_wait<0>();
    } else {
        TS(1);
        const uint32_t jn = 192 + (lane & 3) * 8 + (lane & 16) * 2, ja = tag.x + jn, jb = tag.y + jn;
        const int nr = warp < NCTA / 2 - 64 ? 5 : 4, half = lane >> 4;
        {
            uint32_t c[12], rk[12];
#pragma unroll
            for (int i = 0; i < 12; i++) {
                c[i] = __umulhi(i & 1 ? d2[i >> 1].y : d2[i >> 1].x, 44151u << 9);
                rk[i] = atoms_inc(A_CNT + c[i] * 4);
            }
            TS(2);
            const uint32_t tb = tag.y + (tid << 9), td = tag.x - tag.y;
#pragma unroll
            for (int i = 0; i < 12; i++)
                sts32(A_STG + 4 + c[i] * SPITCH + min(rk[i], (uint32_t)CAP) * 4,
                      (i & 1 ? d2[i >> 1].y : d2[i >> 1].x) + tb + (((i >> 1) * NP * 2 + (i & 1)) << 8) - c[i] * NPC + (rk[i] & 1) * td);
        }
        bar_sync<1, NT>();
        TS(3);
        {
            const uint32_t row = warp * 2 + half, p0 = (lane & 15) * 4;
            uint4* gp = gs->ent + (row * NCTA + cta) * GPITCH + (lane & 15);
            const uint32_t sp = A_STG + row * SPITCH + (lane & 15) * 16;
            uint32_t n[5];
            uint4 v[5];
#pragma unroll
            for (int k = 0; k < 5; k++) {
                n[k] = lds32(A_CNT + min(row + k * 32, NCTA + 1) * 4);
                v[k] = lds128(sp + k * 32 * SPITCH);
            }
            uint32_t big = 0;
#pragma unroll
            for (int k = 0; k < 5; k++) {
                if (p0 - 1 >= n[k]) v[k].x = p0 ? ja : ja + (n[k] << 8);
                if (p0 + 1 > n[k]) v[k].y = jb;
                if (p0 + 2 > n[k]) v[k].z = ja;
                if (p0 + 3 > n[k]) v[k].w = jb;
                stg_rlx128_if(gp + k * 32 * NCTA * GPITCH, v[k], (p0 & ~7u) <= n[k] && (k < 4 || nr == 5));
                if (n[k] >= 64 && (k < 4 || nr == 5)) big |= 1u << k;
            }
            while (__builtin_expect(big != 0, 0)) {
                const int k = __ffs(big) - 1;
                big &= big - 1;
                const uint32_t m = lds32(A_CNT + (row + k * 32) * 4), p = p0 + 64;
                if (p0 < 32 && (p & ~7u) <= m) {
                    uint4 u = lds128(sp + k * 32 * SPITCH + 256);
                    if (p > m) u.x = ja;
                    if (p + 1 > m) u.y = jb;
                    if (p + 2 > m) u.z = ja;
                    if (p + 3 > m) u.w = jb;
                    stg_rlx128(gp + k * 32 * NCTA * GPITCH + 16, u);
                }
            }
            __syncwarp();
        }
        TS(4); TW(0);
        uint32_t w[5][4];
        auto load_w = [&]() {
            mbar_wait(bar_w, 0);
#pragma unroll
            for (int i = 0; i < 5; i++) ldsm4t(w[i], A_WA + hh * 10240 + wofs + i * 2048);
#pragma unroll
            for (int i = 0; i < 5; i++) {
#pragma unroll
                for (int j = 0; j < 4; j++) w[i][j] = bf2h_half(w[i][j]);
                fence_regs(w[i]);
            }
        };
        TS(5);
        const uint4* rp = gs->ent + (cta * NCTA + warp * 2) * GPITCH;
        const uint4* hp = rp + (min(lane >> 1, 4) * 32 + (lane & 1)) * GPITCH;
        rp += half * GPITCH + (lane & 15);
        uint64_t en[10];
        uint32_t rk[20];
#pragma unroll
        for (int i = 0; i < 10; i++) en[i] = ja | (uint64_t)jb << 32;
        const uint32_t row0 = warp * 2 + half, cx = row0 * CHUNK - (tag.x >> 8), cy = row0 * CHUNK - (tag.y >> 8);
        const uint32_t ce[2] = {row0 * 2, min(row0 + 32, 40u) * 2};
        int nl = -1;
        bool fail = false;
        uint32_t pend = (1u << 2 * nr) - 1, todo = (1u << nr) - 1, got = 0;
        for (int it = 0;; it++) {
            const uint2 h = ldg_rlx64_if(hp, (pend >> lane) & 1);
            uint32_t next = 0;
#pragma unroll
            for (int k = 0; k < 5; k++) {
                if (got & (1u << k)) {
                    const uint32_t a = en[2 * k], b = en[2 * k] >> 32, c = en[2 * k + 1], d = en[2 * k + 1] >> 32;
                    if (__builtin_expect(__any_sync(0xffffffffu, ((a ^ tag.x) | (b ^ tag.y) | (c ^ tag.x) | (d ^ tag.y)) >= (1u << 21)), 0)) next |= 1u << k;
                    else {
                        rk[4 * k] = bin_slot(a);
                        rk[4 * k + 1] = bin_slot(b);
                        rk[4 * k + 2] = bin_slot(c);
                        rk[4 * k + 3] = bin_slot(d);
                    }
                }
            }
#pragma unroll
            for (int k = 0; k < 5; k++) {
                if (got & ~next & (1u << k)) {
                    const uint32_t cs = k * 32 * CHUNK + (k < 2 ? ce[k & 1] : 80);
                    uint32_t v[4];
#pragma unroll
                    for (int j = 0; j < 4; j++) {
                        const uint32_t e = en[2 * k + (j >> 1)] >> (j & 1) * 32;
                        v[j] = __funnelshift_r(e, e, 8) + (cs + (j & 1 ? cy : cx));
                        sts32_z(A_BIN + rk[4 * k + j], v[j], rk[4 * k + j] & ~(BIN1 | 255));
                    }
                    en[2 * k] = v[0] | (uint64_t)v[1] << 32;
                    en[2 * k + 1] = v[2] | (uint64_t)v[3] << 32;
                }
            }
            uint32_t hd;
            asm volatile("{\n.reg .u32 t;\nshr.u32 t, %5, 5;\nlop3.b32 t, %1, %2, t, 0xbe;\nlop3.b32 %0, %3, %4, t, 0xbe;\n}" : "=r"(hd) : "r"(h.x), "r"(tag.x), "r"(h.y), "r"(tag.y), "r"(next));
            const bool ok = hd < (1u << 21) && ((pend >> lane) & 1);
            if (ok) nl = (h.x >> 8) & 0x1fff;
            if (ok && nl > CAP) { fail = true; nl = -1; }
            pend &= ~__ballot_sync(0xffffffffu, ok);
            uint32_t seen = 0;
#pragma unroll
            for (int k = 0; k < 5; k++) if (!(pend & (3u << 2 * k))) seen |= 1u << k;
            seen &= todo;
            todo &= ~seen;
            got = next | seen;
            if (!(got | todo)) break;
            if (it >= SPIN) { fail = true; nl = -1; break; }
            if (got) {
#pragma unroll
                for (int k = 0; k < 5; k++) ldg_rlx128_upd(en[2 * k], en[2 * k + 1], rp + k * 32 * GPITCH, (got & (1u << k)) && (lane & 15) * 4 <= __shfl_sync(0xffffffffu, nl, 2 * k + half));
            }
        }
        TW(2);
        uint32_t big = __ballot_sync(0xffffffffu, nl >= 64);
        while (__builtin_expect(big != 0, 0)) {
            const int k = __ffs(big) - 1;
            big &= big - 1;
            const int n = __shfl_sync(0xffffffffu, nl, k), row = (k >> 1) * 32 + warp * 2 + (k & 1);
            if (64 + 4 * lane <= n) {
                uint4 ex;
                bool bad = true;
                for (int it = 0; it < SPIN; it++) {
                    ex = ldg_rlx128_if(gs->ent + (cta * NCTA + row) * GPITCH + 16 + lane, true);
                    bad = ((ex.x ^ tag.x) | (ex.y ^ tag.y) | (ex.z ^ tag.x) | (ex.w ^ tag.y)) >= (1u << 21);
                    if (!bad) break;
                }
                if (bad) fail = true;
                else {
#pragma unroll
                    for (int j = 0; j < 4; j++) {
                        const uint32_t a = j == 0 ? ex.x : j == 1 ? ex.y : j == 2 ? ex.z : ex.w;
                        if (64 + 4 * lane + j <= n) {
                            const uint32_t v = (a << 24) + ((a >> 8) & 0x1fff) + chunk_start(row);
                            sts32(A_BIN + min(bin_slot(a), DUMP), v);
                            deg_inc(v);
                        }
                    }
                }
            }
            __syncwarp();
        }
        TW(3);
        if (fail) sts32(A_MISC, 1);
        load_w();
        bar_sync<12, NT>();
        TS(7);
        if (!fail) {
#pragma unroll
            for (int i = 0; i < 20; i++)
                if (i < 16 || nr == 5) sts32(A_BIN + min(rk[i], DUMP), en[i >> 1] >> (i & 1) * 32);
        }
        bar_arrive<5, NT>();
        TW(7);
        const uint32_t qb = A_QH + hh * QP + (lane & 7) * 128 + ((qch ^ (lane & 7)) << 4);
        uint32_t acc[2][16], h[16], q[4], s[4], tt[WP];
        ldsm4t(q, qb + (lane < 16 ? strm * ((nb - 1) & ~1) : strm * (nb - 2) | 1) * 1024);
        const Sched sc = schedule(lane, nb);
        if (!sc.fail) {
        if (strm ? lane >= sc.B0 && lane < nb - 2 : lane >= 2 && lane <= sc.B0) sts8(A_EV + strm * 128 - 1 + ((strm ? sc.total - sc.start - sc.len : sc.start) >> 6), lane + 32);
        if (lane == 0) { sts8(A_EV + strm * 128 + (strm ? sc.L1 : sc.L), 255); sts32(A_MISC + 4, sc.B0); }
        __syncwarp();
        TS(8);
#pragma unroll
        for (int i = 0; i < 20; i++)
            if (i < 16 || nr == 5) deg_inc(en[i >> 1] >> (i & 1) * 32);
        TW(6);
        TS(10);
#pragma unroll
        for (int i = 0; i < 4; i++) s[i] = 0;
#pragma unroll
        for (int i = 0; i < 5; i++) fence_regs(w[i]);
        fence_regs(q); fence_regs(s);
        uint32_t eva = A_EV + strm * 128, clk = 0;
        const int fd = strm ? 2048 : -2048;
        const uint32_t lox = ((A_XR >> 4) | 0x10000) + strm * 512, loe = ((A_ER >> 4) | 0x10000) + strm * 128, los = ((A_SEL >> 4) | 0x10000) + strm * 128;
        const uint32_t bar_full = A_BAR + strm * 8, bar_empty = bar_full + R * 8;
        auto gemm = [&](int st, uint32_t ph, uint32_t (&d)[16]) {
            mbar_wait(bar_full + st * 16, ph);
            wg_fence();
            mma64h0<HI128>(d, w[0], lox + st * 1024);
            mma64h<1, HI128>(d, w[1], lox + st * 1024 + 2);
            mma64h<1, HI128>(d, w[2], lox + st * 1024 + 4);
            mma64h<1, HI128>(d, w[3], lox + st * 1024 + 6);
            mma64h<1, HI32>(d, w[4], loe + st * 256);
            mma64h<1, HI32>(d, q, los + st * 256);
            wg_commit();
        };
        uint32_t ph = 0;
        gemm(0, 0, acc[0]);
        TS(11); TC(21);
        wg_wait0();
        fence_regs(acc[0]);
        if (lane == 0) mbar_arrive(bar_empty);
#pragma unroll
        for (int i = 0; i < WP; i++) tt[i] = htanh2(acc[0][i]);
        for (;;) {
            TL(min(((eva - A_EV) >> 2) & 31, 15));
            const uint32_t evw = lds32(eva);
#pragma unroll
            for (int st = 0; st < 4; st++) {
                const uint32_t ev = (evw >> (8 * st)) & 255;
                if (__builtin_expect(ev != 0, 0)) {
                    if (ev == 255) goto finished;
                    const uint32_t qa = qb - 32 * 1024 + ev * 1024, fa = qa + fd;
                    if (ev & 1) { stsm2t(fa, s[2], s[3]); ldsm2t(q[2], q[3], qa); s[2] = 0; s[3] = 0; }
                    else { stsm2t(fa, s[0], s[1]); ldsm2t(q[0], q[1], qa); s[0] = 0; s[1] = 0; }
                    fence_regs(s); fence_regs(q);
                }
                uint32_t (&u)[16] = acc[st & 1];
                uint32_t (&v)[16] = acc[(st + 1) & 1];
                if (st == 3) ph ^= 1;
                gemm((st + 1) & 3, ph, v);
#pragma unroll
                for (int i = 0; i < 16; i++) {
                    if (i == SFP) { fence_regs(h); asm volatile("mov.u32 %0, %%clock;" : "=r"(clk)::"memory"); fence_regs(u); }
                    h[i] = hfma2(u[i], i < WP ? tt[i] : htanh2(u[i]), u[i]);
                }
                wg_fence();
#pragma unroll
                for (int k = 0; k < 4; k++) mma16t<HI32>(s, h[4 * k], h[4 * k + 1], h[4 * k + 2], h[4 * k + 3], los + st * 256 + k * 32);
                wg_commit();
                wg_wait1();
                fence_regs(v);
                if (lane == 0) mbar_arrive(bar_empty + ((st + 1) & 3) * 16);
#pragma unroll
                for (int i = 0; i < WP; i++) { tt[i] = htanh2(v[i]); asm volatile("" : "+r"(tt[i])::"memory"); }
                wg_wait0();
                fence_regs(s);
            }
            eva += 4;
        }
    finished:
        TS(12); TC(22);
        {
            const uint2 ms = lds64(A_MISC);
            const bool odd = ms.y & 1;
            const uint32_t l0 = odd ? s[2] : s[0], l1 = odd ? s[3] : s[1], a = qb + ms.y * 1024;
            stsm2t(a + fd / 2, odd ? s[0] : s[2], odd ? s[1] : s[3]);
            if (strm) stsm2t(qb + 24 * 1024, l0, l1);
            bar_sync<3, NT>();
            if (!strm) {
                uint32_t a0, a1;
                ldsm2t(a0, a1, qb + 24 * 1024);
                stsm2t(a, hadd2(l0, a0), hadd2(l1, a1));
            }
            bad = clk & ms.x;
        }
        proxy_fence();
        uint32_t a2[8][4];
        const uint32_t wa = A_W2 + (((lane >> 4) & 1) * 8 + (lane & 7)) * 144 + qch * 16;
#pragma unroll
        for (int i = 0; i < 8; i++) ldsm4t(a2[i], wa + i * 16 * 144);
        const float bo0 = __uint_as_float(lds16(A_B2 + (wq * 16 + (lane >> 2)) * 2) << 16);
        const float bo1 = __uint_as_float(lds16(A_B2 + (wq * 16 + 8 + (lane >> 2)) * 2) << 16);
        float d[24];
#pragma unroll
        for (int i = 0; i < 8; i++) fence_regs(a2[i]);
        bar_sync<6, 512>();
        TS(13);
        const uint32_t lo = ((A_QH >> 4) | 0x10000) + wg * 384;
        wg_fence();
        mma48f<0, HI128>(d, a2[0], lo);
#pragma unroll
        for (int i = 1; i < 8; i++) mma48f<1, HI128>(d, a2[i], lo + (i >> 2) * (QP / 16) + (i & 3) * 2);
        wg_commit();
        float dg[12];
#pragma unroll
        for (int j = 0; j < 6; j++) {
            const uint2 v = lds64(A_DEG + (wg * 48 + j * 8 + (lane & 3) * 2) * 4);
            dg[2 * j] = (float)v.x; dg[2 * j + 1] = (float)v.y;
        }
        wg_wait0();
        fence_regs(d);
        uint32_t r[12];
#pragma unroll
        for (int j = 0; j < 6; j++) {
            const float g0 = dg[2 * j], g1 = dg[2 * j + 1];
            const float v0 = g0 > 0.f ? fmaf(g0, bo0, d[4 * j]) : 0.f, v1 = g1 > 0.f ? fmaf(g1, bo0, d[4 * j + 1]) : 0.f;
            const float v2 = g0 > 0.f ? fmaf(g0, bo1, d[4 * j + 2]) : 0.f, v3 = g1 > 0.f ? fmaf(g1, bo1, d[4 * j + 3]) : 0.f;
            bad |= !(fabsf(v0) + fabsf(v1) + fabsf(v2) + fabsf(v3) < 3.0e38f);
            r[2 * j] = pack_b2(v0, v1); r[2 * j + 1] = pack_b2(v2, v3);
        }
        const uint32_t oa = A_OUT + (wg * 48 + (lane >> 4) * 8 + (lane & 7)) * 128 + ((qch ^ (lane & 7)) << 4);
#pragma unroll
        for (int j = 0; j < 3; j++) stsm4t(oa + j * 2048, r[4 * j], r[4 * j + 1], r[4 * j + 2], r[4 * j + 3]);
        asm volatile("bar.sync %0, 128;" ::"r"(7 + wg) : "memory");
#pragma unroll
        for (int j = 0; j < 3; j++) {
            const int row = wg * 48 + j * 16 + wq * 4 + (lane >> 3);
            const uint4 v = lds128(A_OUT + row * 128 + (((lane ^ row) & 7) << 4));
            if (row < nrows) ((uint4*)out)[(cta * NPC + row) * 8 + (lane & 7)] = v;
        }
        } else bad = 1;
    }
    TS(14);
    if (__syncthreads_or(bad)) slow_path(smem_raw, x, ea, src, dst, w1, b1, w2, b2, out);
}

}

extern "C" void kernel_launch(void* const* d_in, const int* in_sizes, int n_in, void* d_out, int out_size) {
    typedef CUresult (*EncodeFn)(CUtensorMap*, CUtensorMapDataType, cuuint32_t, void*, const cuuint64_t*, const cuuint64_t*, const cuuint32_t*,
                                 const cuuint32_t*, CUtensorMapInterleave, CUtensorMapSwizzle, CUtensorMapL2promotion, CUtensorMapFloatOOBfill);
    static bool init = false;
    static EncodeFn encode = nullptr;
    static void* scratch = nullptr;
    if (!init) {
        cudaFuncSetAttribute(mpnn_kernel, cudaFuncAttributeMaxDynamicSharedMemorySize, SMEM_BYTES);
        void* fn = nullptr;
        cudaDriverEntryPointQueryResult st;
        if (cudaGetDriverEntryPoint("cuTensorMapEncodeTiled", &fn, cudaEnableDefault, &st) == cudaSuccess && st == cudaDriverEntryPointSuccess) encode = (EncodeFn)fn;
        if (cudaGetSymbolAddress(&scratch, g_scratch) != cudaSuccess) scratch = nullptr;
        init = true;
    }
    CUtensorMap map = {};
    const cuuint64_t dims[2] = {128, 144}, strides[1] = {256};
    const cuuint32_t box[2] = {64, 16}, estr[2] = {1, 1};
    const bool have_map = encode && encode(&map, CU_TENSOR_MAP_DATA_TYPE_BFLOAT16, 2, d_in[4], dims, strides, box, estr, CU_TENSOR_MAP_INTERLEAVE_NONE,
                                          CU_TENSOR_MAP_SWIZZLE_128B, CU_TENSOR_MAP_L2_PROMOTION_NONE, CU_TENSOR_MAP_FLOAT_OOB_FILL_NONE) == CUDA_SUCCESS;
    mpnn_kernel<<<NCTA, NT, SMEM_BYTES>>>((const __nv_bfloat16*)d_in[0], (const __nv_bfloat16*)d_in[1], (const int*)d_in[2], (const int*)d_in[3],
                                          (const __nv_bfloat16*)d_in[4], (const __nv_bfloat16*)d_in[5], (const __nv_bfloat16*)d_in[6],
                                          (const __nv_bfloat16*)d_in[7], (__nv_bfloat16*)d_out, have_map ? (Scratch*)scratch : nullptr, map);
}
```

```cpp
#include <cuda_runtime.h>
#include <cuda.h>
#include <cuda_bf16.h>
#include <cuda_fp16.h>
#include <stdint.h>

namespace {

constexpr int N_NODES = 25000;
constexpr int N_EDGES = 800000;
constexpr int NCTA = 132;
constexpr int NPC = 190;
constexpr int NT = 640;
constexpr int NP = 512;
constexpr int CHUNK = 6060;
constexpr int R = 8;
#define GF
#define SFP 3
#define FSL 100
#define FPOS 0
#define WP 1
constexpr int CB = 352;
constexpr int MINB = 128;
constexpr int CAP = 91;
constexpr int SPITCH = 368;
constexpr int GPITCH = 24;
constexpr uint32_t TAGMOD = (1u << 22) - 1;
constexpr uint32_t EMPTY = 0xff000000u;
constexpr int SPIN = 1 << 16;
#define MBSPIN (1 << 22)

constexpr uint32_t SB = 1024;
constexpr uint32_t A_XR = SB;
constexpr uint32_t A_ER = A_XR + R * 8192;
constexpr uint32_t A_SEL = A_ER + R * 2048;
constexpr uint32_t QP = 200 * 128;
constexpr uint32_t A_QH = A_SEL + R * 2048;
constexpr uint32_t A_BIN = A_QH + 2 * QP;
constexpr uint32_t BIN1 = 0xa00, DUMP = BIN1 + 23 * CB * 4;
constexpr uint32_t A_CNT = A_BIN + DUMP + 16;
constexpr uint32_t A_BC = A_CNT + 136 * 4;
constexpr uint32_t A_DEG = A_BC + 32 * 4;
constexpr uint32_t A_EV = A_DEG + 256 * 4;
constexpr uint32_t A_MISC = A_EV + 256;
constexpr uint32_t A_ZEND = A_MISC + 16;
constexpr uint32_t A_TAG = A_ZEND;
constexpr uint32_t A_B1 = A_TAG + 16;
constexpr uint32_t A_B2 = A_B1 + 256;
constexpr uint32_t A_BAR = A_B2 + 128;
constexpr uint32_t A_SS = A_BAR + 20 * 8;
constexpr uint32_t A_END = A_SS + 4 * 512;
constexpr int SMEM_BYTES = A_END - SB;
constexpr uint32_t A_STG = A_XR;
constexpr uint32_t A_WB = A_SEL;
constexpr uint32_t A_WA = A_XR + 49 * 1024;
constexpr uint32_t A_XO = A_QH + QP;
constexpr uint32_t A_W2 = A_BIN;
constexpr uint32_t A_OUT = A_XR;
static_assert(A_STG + (NCTA + 1) * SPITCH + 16 <= A_WA && A_WA + 2 * 10240 <= A_SEL && CB * 4 + 1024 <= BIN1 && BIN1 + 3 * CB * 4 <= 0x2000 && DUMP % 16 == 0 && 24 * CB / 128 < 128, "alias");
static_assert(A_QH % 1024 == 0 && QP % 1024 == 0 && A_WA % 1024 == 0 && A_SEL % 1024 == 0, "align");
static_assert(A_CNT % 16 == 0 && A_ZEND % 16 == 0 && A_B2 % 16 == 0 && A_B1 % 16 == 0 && A_BAR % 8 == 0 && A_BC % 16 == 0 && A_DEG % 8 == 0 && A_MISC % 16 == 0 && A_SS % 16 == 0, "align");
static_assert(SMEM_BYTES <= 199680 && A_ZEND - A_CNT <= 2048, "smem");

struct Scratch {
    uint32_t flag[NCTA * 32];
    uint32_t cnt, pad[31];
    uint4 x16[N_NODES * 8];
    uint4 ent[NCTA * NCTA * GPITCH];
};
__device__ __align__(128) Scratch g_scratch;

#define TL(i)
#define TC(i)
#define TV(i, v)
#define TS(i)
#define TW(i)
#define TWD(i, v)
#define TSX(i, cond)

__device__ __forceinline__ void wg_fence() { asm volatile("wgmma.fence.sync.aligned;" ::: "memory"); }
__device__ __forceinline__ void wg_commit() { asm volatile("wgmma.commit_group.sync.aligned;" ::: "memory"); }
__device__ __forceinline__ void wg_wait0() { asm volatile("wgmma.wait_group.sync.aligned 0;" ::: "memory"); }
__device__ __forceinline__ void wg_wait1() { asm volatile("wgmma.wait_group.sync.aligned 1;" ::: "memory"); }
template <int M> __device__ __forceinline__ void fence_regs(uint32_t (&d)[M]) {
#pragma unroll
    for (int i = 0; i < M; i++) asm volatile("" : "+r"(d[i])::"memory");
}
template <int M> __device__ __forceinline__ void fence_regs(float (&d)[M]) {
#pragma unroll
    for (int i = 0; i < M; i++) asm volatile("" : "+f"(d[i])::"memory");
}
constexpr uint32_t HI128 = 0x40000040;
constexpr uint32_t HI32 = 0xC0000010;
template <int SC, uint32_t HI>
__device__ __forceinline__ void mma64h(uint32_t (&d)[16], const uint32_t (&a)[4], uint32_t lo) {
    asm volatile("{\n.reg .pred p;\n.reg .b64 dsc;\nsetp.ne.b32 p, %21, 0;\nmov.b64 dsc, {%20, %22};\n"
        "wgmma.mma_async.sync.aligned.m64n64k16.f16.f16.f16 {%0, %1, %2, %3, %4, %5, %6, %7, %8, %9, %10, %11, %12, %13, %14, %15}, {%16, %17, %18, %19}, dsc, p, 1, 1, 0;\n}\n"
        : "+r"(d[0]), "+r"(d[1]), "+r"(d[2]), "+r"(d[3]), "+r"(d[4]), "+r"(d[5]), "+r"(d[6]), "+r"(d[7]), "+r"(d[8]), "+r"(d[9]), "+r"(d[10]), "+r"(d[11]), "+r"(d[12]), "+r"(d[13]), "+r"(d[14]), "+r"(d[15])
        : "r"(a[0]), "r"(a[1]), "r"(a[2]), "r"(a[3]), "r"(lo), "n"(SC), "n"(HI));
}
template <uint32_t HI>
__device__ __forceinline__ void mma64h0(uint32_t (&d)[16], const uint32_t (&a)[4], uint32_t lo) {
    asm volatile("{\n.reg .pred p;\n.reg .b64 dsc;\nsetp.ne.b32 p, 0, 0;\nmov.b64 dsc, {%20, %21};\n"
        "wgmma.mma_async.sync.aligned.m64n64k16.f16.f16.f16 {%0, %1, %2, %3, %4, %5, %6, %7, %8, %9, %10, %11, %12, %13, %14, %15}, {%16, %17, %18, %19}, dsc, p, 1, 1, 0;\n}\n"
        : "=r"(d[0]), "=r"(d[1]), "=r"(d[2]), "=r"(d[3]), "=r"(d[4]), "=r"(d[5]), "=r"(d[6]), "=r"(d[7]), "=r"(d[8]), "=r"(d[9]), "=r"(d[10]), "=r"(d[11]), "=r"(d[12]), "=r"(d[13]), "=r"(d[14]), "=r"(d[15])
        : "r"(a[0]), "r"(a[1]), "r"(a[2]), "r"(a[3]), "r"(lo), "n"(HI));
}
template <uint32_t HI>
__device__ __forceinline__ void mma16t(uint32_t (&d)[4], uint32_t a0, uint32_t a1, uint32_t a2, uint32_t a3, uint32_t lo) {
    asm volatile("{\n.reg .pred p;\n.reg .b64 dsc;\nsetp.eq.b32 p, 0, 0;\nmov.b64 dsc, {%8, %9};\n"
        "wgmma.mma_async.sync.aligned.m64n16k16.f16.f16.f16 {%0, %1, %2, %3}, {%4, %5, %6, %7}, dsc, p, 1, 1, 1;\n}\n"
        : "+r"(d[0]), "+r"(d[1]), "+r"(d[2]), "+r"(d[3]) : "r"(a0), "r"(a1), "r"(a2), "r"(a3), "r"(lo), "n"(HI));
}
template <int SC, uint32_t HI>
__device__ __forceinline__ void mma96h(uint32_t (&d)[24], const uint32_t (&a)[4], uint32_t lo) {
    asm volatile("{\n.reg .pred p;\n.reg .b64 dsc;\nsetp.ne.b32 p, %29, 0;\nmov.b64 dsc, {%28, %30};\n"
        "wgmma.mma_async.sync.aligned.m64n96k16.f16.f16.f16 {%0, %1, %2, %3, %4, %5, %6, %7, %8, %9, %10, %11, %12, %13, %14, %15, %16, %17, %18, %19, %20, %21, %22, %23}, {%24, %25, %26, %27}, dsc, p, 1, 1, 0;\n}\n"
        : "+r"(d[0]), "+r"(d[1]), "+r"(d[2]), "+r"(d[3]), "+r"(d[4]), "+r"(d[5]), "+r"(d[6]), "+r"(d[7]), "+r"(d[8]), "+r"(d[9]), "+r"(d[10]), "+r"(d[11]), "+r"(d[12]), "+r"(d[13]), "+r"(d[14]), "+r"(d[15]), "+r"(d[16]), "+r"(d[17]), "+r"(d[18]), "+r"(d[19]), "+r"(d[20]), "+r"(d[21]), "+r"(d[22]), "+r"(d[23])
        : "r"(a[0]), "r"(a[1]), "r"(a[2]), "r"(a[3]), "r"(lo), "n"(SC), "n"(HI));
}
template <int SC, uint32_t HI>
__device__ __forceinline__ void mma48f(float (&d)[24], const uint32_t (&a)[4], uint32_t lo) {
    asm volatile("{\n.reg .pred p;\n.reg .b64 dsc;\nsetp.ne.b32 p, %29, 0;\nmov.b64 dsc, {%28, %30};\n"
        "wgmma.mma_async.sync.aligned.m64n48k16.f32.f16.f16 {%0, %1, %2, %3, %4, %5, %6, %7, %8, %9, %10, %11, %12, %13, %14, %15, %16, %17, %18, %19, %20, %21, %22, %23}, {%24, %25, %26, %27}, dsc, p, 1, 1, 0;\n}\n"
        : "+f"(d[0]), "+f"(d[1]), "+f"(d[2]), "+f"(d[3]), "+f"(d[4]), "+f"(d[5]), "+f"(d[6]), "+f"(d[7]), "+f"(d[8]), "+f"(d[9]), "+f"(d[10]), "+f"(d[11]), "+f"(d[12]), "+f"(d[13]), "+f"(d[14]), "+f"(d[15]), "+f"(d[16]), "+f"(d[17]), "+f"(d[18]), "+f"(d[19]), "+f"(d[20]), "+f"(d[21]), "+f"(d[22]), "+f"(d[23])
        : "r"(a[0]), "r"(a[1]), "r"(a[2]), "r"(a[3]), "r"(lo), "n"(SC), "n"(HI));
}
__device__ __forceinline__ uint32_t hadd2(uint32_t a, uint32_t b) { uint32_t r; asm("add.rn.f16x2 %0, %1, %2;" : "=r"(r) : "r"(a), "r"(b)); return r; }
__device__ __forceinline__ uint32_t hfma2(uint32_t a, uint32_t b, uint32_t c) { uint32_t r; asm("fma.rn.f16x2 %0, %1, %2, %3;" : "=r"(r) : "r"(a), "r"(b), "r"(c)); return r; }
__device__ __forceinline__ uint32_t htanh2(uint32_t a) { uint32_t r; asm("tanh.approx.f16x2 %0, %1;" : "=r"(r) : "r"(a)); return r; }
__device__ __forceinline__ uint32_t pack_h2(float lo, float hi) { uint32_t r; asm("cvt.rn.f16x2.f32 %0, %1, %2;" : "=r"(r) : "f"(hi), "f"(lo)); return r; }
__device__ __forceinline__ uint32_t pack_b2(float lo, float hi) { uint32_t r; asm("cvt.rn.bf16x2.f32 %0, %1, %2;" : "=r"(r) : "f"(hi), "f"(lo)); return r; }
__device__ __forceinline__ uint32_t bf2h(uint32_t v) { return pack_h2(__uint_as_float(v << 16), __uint_as_float(v & 0xffff0000u)); }
__device__ __forceinline__ uint32_t bf2h_half(uint32_t v) { return pack_h2(0.5f * __uint_as_float(v << 16), 0.5f * __uint_as_float(v & 0xffff0000u)); }
__device__ __forceinline__ uint4 bf2h4(uint4 v) { return make_uint4(bf2h(v.x), bf2h(v.y), bf2h(v.z), bf2h(v.w)); }

__device__ __forceinline__ void cp16(uint32_t s, const void* g) { asm volatile("cp.async.cg.shared.global [%0], [%1], 16;" ::"r"(s), "l"(g) : "memory"); }
__device__ __forceinline__ void cp_commit() { asm volatile("cp.async.commit_group;" ::: "memory"); }
template <int N> __device__ __forceinline__ void cp_wait() { asm volatile("cp.async.wait_group %0;" ::"n"(N) : "memory"); }
__device__ __forceinline__ void bulk_g2s(uint32_t s, const void* g, uint32_t bytes, uint32_t bar) {
    asm volatile("cp.async.bulk.shared::cluster.global.mbarrier::complete_tx::bytes [%0], [%1], %2, [%3];" ::"r"(s), "l"(g), "r"(bytes), "r"(bar) : "memory");
}
__device__ __forceinline__ void tma_g2s(uint32_t s, const CUtensorMap* m, int c0, int c1, uint32_t bar) {
    asm volatile("cp.async.bulk.tensor.2d.shared::cluster.global.mbarrier::complete_tx::bytes [%0], [%1, {%2, %3}], [%4];" ::"r"(s), "l"(m), "r"(c0), "r"(c1), "r"(bar) : "memory");
}
__device__ __forceinline__ void l2_prefetch(const void* g, uint32_t bytes) { asm volatile("cp.async.bulk.prefetch.L2.global [%0], %1;" ::"l"(g), "r"(bytes) : "memory"); }
__device__ __forceinline__ void proxy_fence() { asm volatile("fence.proxy.async.shared::cta;" ::: "memory"); }
__device__ __forceinline__ bool mbar_try(uint32_t bar, uint32_t parity) {
    uint32_t ok;
    asm volatile("{\n.reg .pred p;\nmbarrier.try_wait.parity.shared::cta.b64 p, [%1], %2;\nselp.u32 %0, 1, 0, p;\n}" : "=r"(ok) : "r"(bar), "r"(parity) : "memory");
    return ok;
}
__device__ __forceinline__ bool mbar_test(uint32_t bar, uint32_t parity) {
    uint32_t ok;
    asm volatile("{\n.reg .pred p;\nmbarrier.test_wait.parity.shared::cta.b64 p, [%1], %2;\nselp.u32 %0, 1, 0, p;\n}" : "=r"(ok) : "r"(bar), "r"(parity) : "memory");
    return ok;
}
__device__ __forceinline__ void mbar_wait(uint32_t bar, uint32_t parity) {
    if (__builtin_expect(!mbar_try(bar, parity), 0))
        for (int it = 0; it < MBSPIN; it++) if (mbar_try(bar, parity)) break;
}
__device__ __forceinline__ void mbar_arrive(uint32_t bar) { asm volatile("mbarrier.arrive.shared::cta.b64 _, [%0];" ::"r"(bar) : "memory"); }
__device__ __forceinline__ uint32_t lds32(uint32_t a) { uint32_t r; asm volatile("ld.shared.u32 %0, [%1];" : "=r"(r) : "r"(a) : "memory"); return r; }
__device__ __forceinline__ uint32_t lds32_rlx(uint32_t a) { uint32_t r; asm volatile("ld.relaxed.cta.shared.u32 %0, [%1];" : "=r"(r) : "r"(a) : "memory"); return r; }
__device__ __forceinline__ uint32_t lds16(uint32_t a) { uint32_t r; asm volatile("ld.shared.u16 %0, [%1];" : "=r"(r) : "r"(a) : "memory"); return r; }
__device__ __forceinline__ uint2 lds64(uint32_t a) { uint2 r; asm volatile("ld.shared.v2.u32 {%0,%1}, [%2];" : "=r"(r.x), "=r"(r.y) : "r"(a) : "memory"); return r; }
__device__ __forceinline__ uint4 lds128(uint32_t a) { uint4 r; asm volatile("ld.shared.v4.u32 {%0,%1,%2,%3}, [%4];" : "=r"(r.x), "=r"(r.y), "=r"(r.z), "=r"(r.w) : "r"(a) : "memory"); return r; }
__device__ __forceinline__ void sts128(uint32_t a, uint4 v) { asm volatile("st.shared.v4.u32 [%0], {%1,%2,%3,%4};" ::"r"(a), "r"(v.x), "r"(v.y), "r"(v.z), "r"(v.w) : "memory"); }
__device__ __forceinline__ void sts64(uint32_t a, uint32_t x, uint32_t y) { asm volatile("st.shared.v2.u32 [%0], {%1,%2};" ::"r"(a), "r"(x), "r"(y) : "memory"); }
__device__ __forceinline__ void sts32(uint32_t a, uint32_t v) { asm volatile("st.shared.u32 [%0], %1;" ::"r"(a), "r"(v) : "memory"); }
__device__ __forceinline__ void sts16(uint32_t a, uint32_t v) { asm volatile("st.shared.u16 [%0], %1;" ::"r"(a), "r"(v) : "memory"); }
__device__ __forceinline__ void sts8(uint32_t a, uint32_t v) { asm volatile("st.shared.u8 [%0], %1;" ::"r"(a), "r"(v) : "memory"); }
__device__ __forceinline__ void sts32_z(uint32_t a, uint32_t v, uint32_t z) {
    asm volatile("{\n.reg .pred p;\nsetp.eq.u32 p, %2, 0;\n@p st.relaxed.cta.shared.u32 [%0], %1;\n}" ::"r"(a), "r"(v), "r"(z) : "memory");
}
__device__ __forceinline__ uint32_t atoms_inc(uint32_t a) { uint32_t r; asm volatile("atom.shared.add.u32 %0, [%1], 1;" : "=r"(r) : "r"(a) : "memory"); return r; }
__device__ __forceinline__ uint32_t bin_slot(uint32_t e) {
    uint32_t r;
    asm volatile("atom.shared.add.u32 %0, [%1], 4;" : "=r"(r) : "r"(A_BC + ((e >> 1) & 0x7c)) : "memory");
    return r;
}
__device__ __forceinline__ uint32_t bin_base(int b, int nb) { return b == 0 ? 0u : BIN1 + (b == nb - 1 ? 0 : b == 1 ? 1 : b == nb - 2 ? 2 : b + 1) * CB * 4; }
__device__ __forceinline__ void deg_inc(uint32_t v) { asm volatile("red.shared.add.u32 [%0], 1;" ::"r"(A_DEG + (v >> 22)) : "memory"); }
__device__ __forceinline__ uint32_t ldg_rlx32(const void* p) { uint32_t r; asm volatile("ld.relaxed.gpu.global.u32 %0, [%1];" : "=r"(r) : "l"(p) : "memory"); return r; }
#define LDI "ld.relaxed.gpu.global.v2.u32"
__device__ __forceinline__ int2 ldg64(const void* p) { int2 r; asm volatile(LDI " {%0,%1}, [%2];" : "=r"(r.x), "=r"(r.y) : "l"(p) : "memory"); return r; }
__device__ __forceinline__ void ldg64_if(int2& r, const void* p, bool on) {
    asm volatile("{\n.reg .pred p;\nsetp.ne.u32 p, %3, 0;\n@p " LDI " {%0,%1}, [%2];\n}" : "+r"(r.x), "+r"(r.y) : "l"(p), "r"((uint32_t)on) : "memory");
}
__device__ __forceinline__ uint4 ldg_rlx128_if(const void* p, bool on) {
    uint4 r;
    asm volatile("{\n.reg .pred p;\n.reg .b64 a, b;\nsetp.ne.u32 p, %5, 0;\n@p ld.relaxed.gpu.global.v2.b64 {a, b}, [%4];\nmov.b64 {%0,%1}, a;\nmov.b64 {%2,%3}, b;\n}"
                 : "=r"(r.x), "=r"(r.y), "=r"(r.z), "=r"(r.w) : "l"(p), "r"((uint32_t)on) : "memory");
    return r;
}
__device__ __forceinline__ void ldg_rlx128_upd(uint64_t& a, uint64_t& b, const void* p, bool on) {
    asm volatile("{\n.reg .pred p;\nsetp.ne.u32 p, %3, 0;\n@p ld.relaxed.gpu.global.v2.b64 {%0, %1}, [%2];\n}" : "+l"(a), "+l"(b) : "l"(p), "r"((uint32_t)on) : "memory");
}
__device__ __forceinline__ uint2 ldg_rlx64_if(const void* p, bool on) {
    uint64_t a = 0;
    asm volatile("{\n.reg .pred p;\nsetp.ne.u32 p, %2, 0;\n@p ld.relaxed.gpu.global.b64 %0, [%1];\n}" : "+l"(a) : "l"(p), "r"((uint32_t)on) : "memory");
    return make_uint2((uint32_t)a, (uint32_t)(a >> 32));
}
__device__ __forceinline__ uint4 ldg_acq128(const void* p) {
    uint4 r;
    asm volatile("ld.acquire.gpu.global.v4.u32 {%0,%1,%2,%3}, [%4];" : "=r"(r.x), "=r"(r.y), "=r"(r.z), "=r"(r.w) : "l"(p) : "memory");
    return r;
}
__device__ __forceinline__ void stg_rlx32(void* p, uint32_t v) { asm volatile("st.relaxed.gpu.global.u32 [%0], %1;" ::"l"(p), "r"(v) : "memory"); }
__device__ __forceinline__ void stg_rlx128(void* p, uint4 v) {
    asm volatile("{\n.reg .b64 a, b;\nmov.b64 a, {%1,%2};\nmov.b64 b, {%3,%4};\nst.relaxed.gpu.global.v2.b64 [%0], {a, b};\n}" ::"l"(p), "r"(v.x), "r"(v.y), "r"(v.z), "r"(v.w) : "memory");
}
__device__ __forceinline__ void stg_rlx128_if(void* p, uint4 v, bool on) {
    asm volatile("{\n.reg .pred p;\n.reg .b64 a, b;\nsetp.ne.u32 p, %5, 0;\nmov.b64 a, {%1,%2};\nmov.b64 b, {%3,%4};\n@p st.relaxed.gpu.global.v2.b64 [%0], {a, b};\n}" ::"l"(p), "r"(v.x), "r"(v.y), "r"(v.z), "r"(v.w), "r"((uint32_t)on) : "memory");
}
__device__ __forceinline__ void ldsm4t(uint32_t (&r)[4], uint32_t a) {
    asm volatile("ldmatrix.sync.aligned.m8n8.x4.trans.shared.b16 {%0,%1,%2,%3}, [%4];" : "=r"(r[0]), "=r"(r[1]), "=r"(r[2]), "=r"(r[3]) : "r"(a) : "memory");
}
__device__ __forceinline__ void ldsm2t(uint32_t& r0, uint32_t& r1, uint32_t a) {
    asm volatile("ldmatrix.sync.aligned.m8n8.x2.trans.shared.b16 {%0,%1}, [%2];" : "=r"(r0), "=r"(r1) : "r"(a) : "memory");
}
__device__ __forceinline__ void stsm2t(uint32_t a, uint32_t r0, uint32_t r1) {
    asm volatile("stmatrix.sync.aligned.m8n8.x2.trans.shared.b16 [%0], {%1,%2};" ::"r"(a), "r"(r0), "r"(r1) : "memory");
}
__device__ __forceinline__ void stsm4t(uint32_t a, uint32_t r0, uint32_t r1, uint32_t r2, uint32_t r3) {
    asm volatile("stmatrix.sync.aligned.m8n8.x4.trans.shared.b16 [%0], {%1,%2,%3,%4};" ::"r"(a), "r"(r0), "r"(r1), "r"(r2), "r"(r3) : "memory");
}
template <int ID, int N> __device__ __forceinline__ void bar_sync() { asm volatile("bar.sync %0, %1;" ::"n"(ID), "n"(N) : "memory"); }
template <int ID, int N> __device__ __forceinline__ void bar_arrive() { asm volatile("bar.arrive %0, %1;" ::"n"(ID), "n"(N) : "memory"); }
__device__ __forceinline__ uint32_t scan_up(uint32_t v) {
#pragma unroll
    for (int o = 1; o < 32; o <<= 1)
        asm volatile("{\n.reg .pred p;\n.reg .u32 t;\nshfl.sync.up.b32 t|p, %0, %1, 0, -1;\n@p add.u32 %0, %0, t;\n}" : "+r"(v) : "r"(o));
    return v;
}
__device__ __forceinline__ float bf2f(const __nv_bfloat16* p) { return __bfloat162float(*p); }

__device__ __forceinline__ int chunk_start(int c) { return c * CHUNK + min(c, 40) * 2; }
static_assert(NCTA * CHUNK + 80 == N_EDGES && CHUNK / 2 + 1 <= 6 * NP && CHUNK / 2 >= 5 * NP, "chunks");

struct Sched { uint32_t len, start, total; int L, L1, B0; bool fail; };
__device__ __forceinline__ Sched schedule(int lane, int nb) {
    Sched r;
    const uint32_t n = (lds32(A_BC + lane * 4) - bin_base(lane, nb)) >> 2, f = lds32(A_MISC);
    r.len = lane < nb ? max(n, (uint32_t)MINB) : 0u;
    const uint32_t end = scan_up(r.len);
    r.start = end - r.len;
    r.total = __shfl_sync(0xffffffffu, end, 31);
    r.L = (r.total + 127) >> 7;
    r.L1 = ((r.total + 63) >> 6) - r.L;
    r.B0 = __popc(__ballot_sync(0xffffffffu, end <= 64u * r.L));
    r.fail = __any_sync(0xffffffffu, r.len > CB || f);
    return r;
}
static_assert(64 * ((14 * MINB + 127) / 128) >= 2 * CB && 14 * MINB / 2 - 64 > 2 * CB && 14 * MINB / 2 - 64 - CB >= 7 * 64, "block B0 is never among the first two of a stream");

__device__ __noinline__ void slow_path(uint8_t* sp, const __nv_bfloat16* x, const __nv_bfloat16* ea, const int* src, const int* dst,
                                       const __nv_bfloat16* w1, const __nv_bfloat16* b1, const __nv_bfloat16* w2,
                                       const __nv_bfloat16* b2, __nv_bfloat16* out) {
    const int tid = threadIdx.x, lane = tid & 31, warp = tid >> 5, cta = blockIdx.x;
    const int nrows = min(NPC, N_NODES - cta * NPC);
    float* hs = (float*)sp;
    __nv_bfloat16* w1s = (__nv_bfloat16*)(sp + 192 * 128 * 4);
    int* dg = (int*)(sp + 192 * 128 * 4 + 144 * 128 * 2);
    __syncthreads();
    for (int i = tid; i < 192 * 128; i += NT) hs[i] = 0.f;
    for (int i = tid; i < 144 * 128; i += NT) w1s[i] = w1[i];
    for (int i = tid; i < 192; i += NT) dg[i] = 0;
    __syncthreads();
    float bb[4];
    for (int j = 0; j < 4; j++) bb[j] = bf2f(b1 + lane * 4 + j);
    for (int i0 = warp * 32; i0 < N_EDGES; i0 += NT) {
        const int mine = dst[i0 + lane] - cta * NPC;
        uint32_t hit = __ballot_sync(0xffffffffu, (unsigned)mine < (unsigned)nrows);
        while (hit) {
            const int b = __ffs(hit) - 1;
            hit &= hit - 1;
            const int eid = i0 + b, dl = __shfl_sync(0xffffffffu, mine, b), s = src[eid];
            float v[5];
            v[0] = bf2f(x + s * 64 + lane); v[1] = bf2f(x + s * 64 + 32 + lane);
            v[2] = bf2f(x + (cta * NPC + dl) * 64 + lane); v[3] = bf2f(x + (cta * NPC + dl) * 64 + 32 + lane);
            v[4] = lane < 16 ? bf2f(ea + (size_t)eid * 16 + lane) : 0.f;
            float z[4] = {bb[0], bb[1], bb[2], bb[3]};
#pragma unroll
            for (int c = 0; c < 5; c++) {
                for (int kk = 0; kk < (c == 4 ? 16 : 32); kk++) {
                    float a = __shfl_sync(0xffffffffu, v[c], kk);
                    const __nv_bfloat16* wr = w1s + (c * 32 + kk) * 128 + lane * 4;
#pragma unroll
                    for (int j = 0; j < 4; j++) z[j] = fmaf(a, __bfloat162float(wr[j]), z[j]);
                }
            }
#pragma unroll
            for (int j = 0; j < 4; j++) atomicAdd(&hs[dl * 128 + lane * 4 + j], z[j] / (1.f + expf(-z[j])));
            if (lane == 0) atomicAdd(&dg[dl], 1);
        }
    }
    __syncthreads();
    for (int i = tid; i < nrows * 64; i += NT) {
        int n = i >> 6, d = i & 63;
        float a = 0.f;
        if (dg[n] > 0) {
            a = (float)dg[n] * bf2f(b2 + d);
            for (int h = 0; h < 128; h++) a = fmaf(hs[n * 128 + h], bf2f(w2 + h * 64 + d), a);
        }
        out[(size_t)(cta * NPC + n) * 64 + d] = __float2bfloat16(a);
    }
}

__global__ void __launch_bounds__(NT, 1)
mpnn_kernel(const __nv_bfloat16* __restrict__ x, const __nv_bfloat16* __restrict__ ea, const int* __restrict__ src,
            const int* __restrict__ dst, const __nv_bfloat16* __restrict__ w1, const __nv_bfloat16* __restrict__ b1,
            const __nv_bfloat16* __restrict__ w2, const __nv_bfloat16* __restrict__ b2, __nv_bfloat16* __restrict__ out,
            Scratch* __restrict__ gs, const __grid_constant__ CUtensorMap w1map) {
    extern __shared__ uint8_t smem_raw[];
    const int tid = threadIdx.x, lane = tid & 31;
    __builtin_assume(tid < NT);
    const int warp = __shfl_sync(0xffffffffu, tid >> 5, 0);
    const int cta = blockIdx.x;
    const int nrows = min(NPC, N_NODES - cta * NPC), nb = (nrows + 7) >> 3;
    const int e0 = chunk_start(cta);
    const int nv2 = CHUNK / 2 + (cta < 40);
    if ((uint32_t)__cvta_generic_to_shared(smem_raw) != SB || !gs) { slow_path(smem_raw, x, ea, src, dst, w1, b1, w2, b2, out); return; }
    constexpr uint32_t bar_w = A_BAR + R * 16, bar_x = bar_w + 8, bar_r = bar_x + 8;
    const int wg = warp >> 2, wq = warp & 3, hh = wg & 1, strm = wg >> 1;
    const uint32_t qch = wq * 2 + ((lane >> 3) & 1);
    const uint32_t wofs = (((lane >> 4) & 1) * 8 + (lane & 7)) * 128 + ((qch ^ (lane & 7)) << 4);
    int bad = 0;
    TS(0);

    int2 d2[6];
    const int pt = tid - NP;
    if (wg == 4) {
        uint32_t cnt0;
        if (pt == 64) cnt0 = ldg_rlx32(&gs->cnt);
        if (pt == 96) {
#pragma unroll
            for (int i = 0; i < 2 * R + 3; i++) asm volatile("mbarrier.init.shared::cta.b64 [%0], %1;" ::"r"(A_BAR + i * 8), "r"(i < R ? 2 : i < 2 * R ? 8 : i < 2 * R + 2 ? 1 : NT / 32) : "memory");
            proxy_fence();
            asm volatile("mbarrier.arrive.expect_tx.shared::cta.b64 _, [%0], %1;" ::"r"(bar_w), "r"(144 * 256 + 256 + 128) : "memory");
            asm volatile("mbarrier.arrive.expect_tx.shared::cta.b64 _, [%0], %1;" ::"r"(bar_x), "r"(nrows * 128) : "memory");
        }
        __syncwarp();
        stg_rlx128_if((uint4*)gs->flag + cta * 8 + (lane & 1), make_uint4(0, 0, 0, 0), pt < 2);
        if (pt < (int)(A_ZEND - A_CNT) / 16) sts128(A_CNT + pt * 16, make_uint4(0, 0, 0, 0));
        if (pt == 64) {
            const uint32_t tag = cnt0 / NCTA + 1;
            sts64(A_TAG, tag << 21, tag >> 11 << 21);
        }
    } else {
        const int2* dp = (const int2*)(dst + e0) + tid;
        d2[5] = make_int2(NCTA * NPC, NCTA * NPC);
#pragma unroll
        for (int r = 0; r < 5; r++) d2[r] = ldg64(dp + r * NP);
        ldg64_if(d2[5], dp + 5 * NP, tid < nv2 - 5 * NP);
        stg_rlx128_if(gs->ent + ((tid >> 1) * NCTA + cta) * GPITCH + (lane & 1), make_uint4(0, 0, 0, 0), tid < 2 * NCTA);
    }
    __syncthreads();
    const uint2 tag = lds64(A_TAG);
    if (wg == 4) {
        const uint32_t tagw = tag.x | tag.y >> 11;
        if (warp == 19) {
            if (lane == 0) {
                bulk_g2s(A_XO, x + cta * NPC * 64, nrows * 128, bar_x);
                asm volatile("red.relaxed.gpu.global.inc.u32 [%0], %1;" ::"l"(&gs->cnt), "r"(NCTA * TAGMOD - 1) : "memory");
            }
            TSX(15, lane == 0);
            __syncwarp();
            if (lane < 18) {
                int i = lane + cta % 18;
                i = i >= 18 ? i - 18 : i;
                const int h = i & 1, rb = i >> 1;
                tma_g2s(rb >= 4 && rb < 8 ? A_WB + h * 8192 + (rb - 4) * 2048 : A_WA + h * 10240 + min(rb, 4) * 2048, &w1map, h * 64, rb * 16, bar_w);
            } else if (lane < 20) bulk_g2s(lane == 18 ? A_B1 : A_B2, lane == 18 ? b1 : b2, lane == 18 ? 256 : 128, bar_w);
            else if (lane == 20) l2_prefetch(w2, 128 * 64 * 2);
            __syncwarp();
        }
        if (warp == 16) sts32(A_BC + lane * 4, lane < 24 ? bin_base(lane, nb) : DUMP);
#pragma unroll 1
        for (uint32_t a = A_BIN + pt * 16; a < A_BIN + DUMP; a += 2048) sts128(a, make_uint4(EMPTY, EMPTY, EMPTY, EMPTY));
        bar_arrive<1, NT>();
        mbar_wait(bar_x, 0);
        TW(0);
        const uint32_t xo = A_XO + (pt >> 3) * 128 + (((pt ^ (pt >> 3)) & 7) << 4);
        {
            uint4 xr[12];
#pragma unroll
            for (int r = 0; r < 12; r++) xr[r] = lds128(A_XO + (r * 128 + pt) * 16);
            __syncwarp();
#pragma unroll
            for (int r = 0; r < 12; r++) {
                const bool in = r * 128 + pt < nrows * 8;
                const uint4 v = in ? bf2h4(xr[r]) : make_uint4(0, 0, 0, 0);
                sts128(xo + r * 2048, v);
                if (in) gs->x16[cta * NPC * 8 + r * 128 + pt] = v;
            }
        }
        bar_arrive<2, 160>();
        proxy_fence();
        mbar_wait(bar_w, 0);
        bar_sync<4, 128>();
        TW(1);
#pragma unroll 1
        for (int h = 0; h < 2; h++) {
            uint32_t wb[4][4], acc[2][24];
#pragma unroll
            for (int i = 0; i < 4; i++) ldsm4t(wb[i], A_WB + h * 8192 + wofs + i * 2048);
            const uint32_t bl0 = lds16(A_B1 + (h * 64 + wq * 16 + (lane >> 2)) * 2), bl1 = lds16(A_B1 + (h * 64 + wq * 16 + 8 + (lane >> 2)) * 2);
#pragma unroll
            for (int i = 0; i < 4; i++)
#pragma unroll
                for (int j = 0; j < 4; j++) wb[i][j] = bf2h_half(wb[i][j]);
            const uint32_t bq0 = bf2h_half(bl0 * 0x10001u), bq1 = bf2h_half(bl1 * 0x10001u);
#pragma unroll
            for (int i = 0; i < 4; i++) fence_regs(wb[i]);
            wg_fence();
#pragma unroll
            for (int n = 0; n < 2; n++) {
                const uint32_t lo = ((A_XO >> 4) | 0x10000) + n * 768;
                mma96h<0, HI128>(acc[n], wb[0], lo);
                mma96h<1, HI128>(acc[n], wb[1], lo + 2);
                mma96h<1, HI128>(acc[n], wb[2], lo + 4);
                mma96h<1, HI128>(acc[n], wb[3], lo + 6);
            }
            wg_commit();
            wg_wait0();
            fence_regs(acc[0]); fence_regs(acc[1]);
            if (h) {
                bar_sync<4, 128>();
            }
#pragma unroll
            for (int n = 0; n < 2; n++)
#pragma unroll
                for (int j = 0; j < 6; j++)
                    stsm4t(A_QH + h * QP + n * 12288 + wofs + j * 2048, hadd2(acc[n][4 * j], bq0), hadd2(acc[n][4 * j + 1], bq1), hadd2(acc[n][4 * j + 2], bq0), hadd2(acc[n][4 * j + 3], bq1));
        }
        if (pt == 64) l2_prefetch(src + cta * 6064, min(6064, N_EDGES - cta * 6064) * 4);
        TW(2);
        const int par = wq >> 1, hf = wq & 1, gq = lane >> 3, cp = (lane >> 1) & 3;
        const uint32_t sel = A_SEL + hf * 2048 + (par * 32 + lane) * 32 + ((lane >> 2) & 1) * 16;
#pragma unroll
        for (int r = 0; r < 8; r++) sts128(A_SEL + hf * 2048 + par * 1024 + (r >> 1) * 4096 + (r & 1) * 512 + lane * 16, make_uint4(0, 0, 0, 0));
        const uint32_t bar_full = A_BAR + hf * 8, bar_empty = bar_full + R * 8;
        uint32_t xd[8];
#pragma unroll
        for (int c = 0; c < 8; c++) xd[c] = A_XR + hf * 8192 + (par * 32 + gq * 8) * 128 + (((lane & 7) ^ c) << 4);
        fence_regs(xd);
        uint32_t ed0 = A_ER + hf * 2048 + (par * 32 + gq * 8 + cp) * 32 + (lane & 1) * 16, ed1 = (ed0 ^ 16) + 128;
        const uint32_t sw = A_SS + wq * 128 + lane * 4, sr = A_SS + wq * 128 + gq * 32;
        const char* xg = (const char*)gs->x16 + (lane & 7) * 16;
        const char* eg = (const char*)ea + (lane & 1) * 16;
        const char* sp = (const char*)src;
        int bi = hf ? nb - 1 : 0;
        uint32_t ta = A_BIN + hf * BIN1 + (par * 32 + lane) * 4;
        asm volatile("" : "+l"(xg), "+l"(eg), "+l"(sp), "+r"(ed0), "+r"(ed1), "+r"(ta));
        uint32_t prev[4] = {sel, sel, sel, sel}, own[4], col[4];
        auto issue_e = [&](int st, uint32_t e) {
            const uint32_t e0 = __shfl_sync(0xffffffffu, e, gq * 8 + cp), e1 = __shfl_sync(0xffffffffu, e, gq * 8 + cp + 4);
            cp16(ed0 + st * 4096, eg + (size_t)(e0 & 0xfffff) * 32);
            cp16(ed1 + st * 4096, eg + (size_t)(e1 & 0xfffff) * 32);
            col[st] = e;
        };
        auto issue_x = [&](int st, const uint4& a0, const uint4& a1) {
            const uint32_t a[8] = {a0.x, a0.y, a0.z, a0.w, a1.x, a1.y, a1.z, a1.w};
#pragma unroll
            for (int i = 0; i < 8; i++) cp16(xd[i] + st * 16384 + i * 128, xg + (size_t)a[i] * 128);
        };
        auto fetch_src = [&](int slot, uint32_t e) {
            asm volatile("cp.async.ca.shared.global [%0], [%1], 4;" ::"r"(sw + slot * 512), "l"(sp + (size_t)(e & 0xfffff) * 4) : "memory");
        };
        auto finish = [&](int u) {
            const uint4 v0 = lds128(ed0 + u * 4096), v1 = lds128(ed1 + u * 4096);
            sts16(prev[u] + u * 4096, 0);
            prev[u] = sel ^ ((col[u] >> 23) & 0x1e);
            sts16(prev[u] + u * 4096, col[u] < (192u << 24) ? 0x3c00 : 0);
            deg_inc(col[u]);
            sts128(ed0 + u * 4096, bf2h4(v0));
            sts128(ed1 + u * 4096, bf2h4(v1));
            proxy_fence();
            __syncwarp();
            if (lane == 0) mbar_arrive(bar_full + u * 16);
        };
        __syncwarp();
        if (lane == 0) mbar_arrive(bar_r);
        auto flags = [&]() {
            const uint32_t* fp = gs->flag + (wq * 33 + lane) * 32;
#pragma unroll 1
            for (int it = 0;; it++) {
                const uint32_t f0 = ldg_rlx32(fp), f1 = ldg_rlx32(gs->flag + (wq * 33 + 32) * 32);
                if (__all_sync(0xffffffffu, f0 == tagw && f1 == tagw)) break;
                if (it >= SPIN) { bad = 1; break; }
                __nanosleep(FSL);
            }
            asm volatile("fence.acquire.gpu;" ::: "memory");
            TSX(17, tid == 512);
        };
        bar_sync<12, NT>();
        TW(7);
#pragma unroll 1
        for (int it = 0; it < MBSPIN; it++) {
            const bool all = mbar_test(bar_r, 0);
            col[0] = lds32_rlx(ta);
            col[1] = lds32_rlx(ta + 256);
            if (__all_sync(0xffffffffu, all || (col[0] != EMPTY && col[1] != EMPTY))) break;
            __nanosleep(40);
        }
        {
            const uint32_t ea = ta + (gq * 8 + cp - lane) * 4;
            const uint32_t a0 = lds32_rlx(ea), a1 = lds32_rlx(ea + 16), a2 = lds32_rlx(ea + 256), a3 = lds32_rlx(ea + 256 + 16);
            fetch_src(0, col[0]);
            fetch_src(1, col[1]);
            cp_commit();
            TWD(0, col[1]);
            cp16(ed0, eg + (size_t)(a0 & 0xfffff) * 32);
            cp16(ed1, eg + (size_t)(a1 & 0xfffff) * 32);
            cp16(ed0 + 4096, eg + (size_t)(a2 & 0xfffff) * 32);
            cp16(ed1 + 4096, eg + (size_t)(a3 & 0xfffff) * 32);
            cp_commit();
            ta += 256;
        }
        flags();
        cp_wait<1>();
        bar_sync<4, 128>();
        TWD(2, ta);
        issue_x(0, lds128(sr), lds128(sr + 16));
        cp_commit();
        issue_x(1, lds128(sr + 512), lds128(sr + 512 + 16));
        cp_commit();
        TW(4);
        mbar_wait(bar_r, 0);
        TSX(9, tid == 512);
        uint32_t bs = A_BIN + bin_base(lane, nb), be = max(A_BIN + lds32(A_BC + lane * 4), bs + MINB * 4);
        const int dir = hf ? -1 : 1;
        uint32_t nx = __shfl_sync(0xffffffffu, be, bi);
        auto next_entry = [&]() {
            ta += 256;
            while (__builtin_expect(__any_sync(0xffffffffu, ta >= nx), 0)) {
                const bool c = ta >= nx;
                if (c) bi += dir;
                const uint32_t s2 = __shfl_sync(0xffffffffu, bs, bi), e2 = __shfl_sync(0xffffffffu, be, bi);
                if (c) { ta += s2 - nx; nx = e2; }
            }
            return lds32(ta);
        };
        own[2] = next_entry();
        own[3] = next_entry();
        fetch_src(2, own[2]);
        fetch_src(3, own[3]);
        cp_commit();
        issue_e(2, own[2]);
        issue_e(3, own[3]);
        cp_commit();
        TW(1);
        cp_wait<3>();
        TW(5);
        finish(0);
        cp_wait<2>();
        finish(1);
        TW(6);
        bar_sync<5, NT>();
        TW(3);
        own[0] = next_entry();
        own[1] = next_entry();
        fetch_src(0, own[0]);
        fetch_src(1, own[1]);
        cp_commit();
        own[2] = next_entry();
        cp_wait<2>();
        __syncwarp();
        issue_x(2, lds128(sr + 1024), lds128(sr + 1024 + 16));
        cp_commit();
        issue_x(3, lds128(sr + 1536), lds128(sr + 1536 + 16));
        fetch_src(2, own[2]);
        cp_commit();
        const Sched sc = schedule(lane, nb);
        if (!sc.fail) {
            const int L = hf ? sc.L1 : sc.L;
            if (lane == sc.B0) { const uint32_t cut = bs + (64 * sc.L - sc.start) * 4; if (hf) bs = cut; else be = cut; }
            if (lane == sc.B0 + dir) { bs = A_BIN + CB * 4; be = ~0u; }
            cp_wait<2>();
            __syncwarp();
            uint32_t ph = 1;
            for (int j = L;; j -= 4) {
#pragma unroll
                for (int u = 2; u < 6; u++) {
                    if (j == u) goto done;
                    if (u == 2) ph ^= 1;
                    const int st = (u + 2) & 3;
                    if (j > u + 2) {
                        const uint32_t es = next_entry();
                        const uint4 a0 = lds128(sr + st * 512), a1 = lds128(sr + st * 512 + 16);
                        fetch_src((st + 3) & 3, es);
                        mbar_wait(bar_empty + st * 16, ph);
                        issue_e(st, own[st]);
                        issue_x(st, a0, a1);
                        own[(st + 3) & 3] = es;
                    } else mbar_wait(bar_empty + st * 16, ph);
                    cp_commit();
                    cp_wait<2>();
                    finish(u & 3);
                }
            }
        done:
            if (lane == 0) mbar_arrive(bar_full + (L & 3) * 16);
            TSX(18, tid == 512);
            uint4 v[8];
#pragma unroll
            for (int i = 0; i < 8; i++) v[i] = __ldg((const uint4*)w2 + i * 128 + pt);
            bar_sync<4, 128>();
#pragma unroll
            for (int i = 0; i < 8; i++) sts128(A_W2 + (i * 16 + (pt >> 3)) * 144 + (pt & 7) * 16, bf2h4(v[i]));
            bar_arrive<3, NT>();
        } else bad = 1;
        cp_wait<0>();
    } else {
        TS(1);
        const uint32_t jn = 192 + (lane & 3) * 8 + (lane & 16) * 2, ja = tag.x + jn, jb = tag.y + jn;
        const int nr = warp < NCTA / 2 - 64 ? 5 : 4, half = lane >> 4;
        {
            uint32_t c[12], rk[12];
#pragma unroll
            for (int i = 0; i < 12; i++) {
                c[i] = __umulhi(i & 1 ? d2[i >> 1].y : d2[i >> 1].x, 44151u << 9);
                rk[i] = atoms_inc(A_CNT + c[i] * 4);
            }
            TS(2);
            const uint32_t tb = tag.y + (tid << 9), td = tag.x - tag.y;
#pragma unroll
            for (int i = 0; i < 12; i++)
                sts32(A_STG + 4 + c[i] * SPITCH + min(rk[i], (uint32_t)CAP) * 4,
                      (i & 1 ? d2[i >> 1].y : d2[i >> 1].x) + tb + (((i >> 1) * NP * 2 + (i & 1)) << 8) - c[i] * NPC + (rk[i] & 1) * td);
        }
        bar_sync<1, NT>();
        TS(3);
        {
            const uint32_t row = warp * 2 + half, p0 = (lane & 15) * 4;
            uint4* gp = gs->ent + (row * NCTA + cta) * GPITCH + (lane & 15);
            const uint32_t sp = A_STG + row * SPITCH + (lane & 15) * 16;
            uint32_t n[5];
            uint4 v[5];
#pragma unroll
            for (int k = 0; k < 5; k++) {
                n[k] = lds32(A_CNT + min(row + k * 32, NCTA + 1) * 4);
                v[k] = lds128(sp + k * 32 * SPITCH);
            }
            uint32_t big = 0;
#pragma unroll
            for (int k = 0; k < 5; k++) {
                if (p0 - 1 >= n[k]) v[k].x = p0 ? ja : ja + (n[k] << 8);
                if (p0 + 1 > n[k]) v[k].y = jb;
                if (p0 + 2 > n[k]) v[k].z = ja;
                if (p0 + 3 > n[k]) v[k].w = jb;
                stg_rlx128_if(gp + k * 32 * NCTA * GPITCH, v[k], (p0 & ~7u) <= n[k] && (k < 4 || nr == 5));
                if (n[k] >= 64 && (k < 4 || nr == 5)) big |= 1u << k;
            }
            while (__builtin_expect(big != 0, 0)) {
                const int k = __ffs(big) - 1;
                big &= big - 1;
                const uint32_t m = lds32(A_CNT + (row + k * 32) * 4), p = p0 + 64;
                if (p0 < 32 && (p & ~7u) <= m) {
                    uint4 u = lds128(sp + k * 32 * SPITCH + 256);
                    if (p > m) u.x = ja;
                    if (p + 1 > m) u.y = jb;
                    if (p + 2 > m) u.z = ja;
                    if (p + 3 > m) u.w = jb;
                    stg_rlx128(gp + k * 32 * NCTA * GPITCH + 16, u);
                }
            }
            __syncwarp();
        }
        TS(4); TW(0);
        uint32_t w[5][4];
        auto load_w = [&]() {
            mbar_wait(bar_w, 0);
#pragma unroll
            for (int i = 0; i < 5; i++) ldsm4t(w[i], A_WA + hh * 10240 + wofs + i * 2048);
#pragma unroll
            for (int i = 0; i < 5; i++) {
#pragma unroll
                for (int j = 0; j < 4; j++) w[i][j] = bf2h_half(w[i][j]);
                fence_regs(w[i]);
            }
        };
        load_w();
        bar_arrive<12, NT>();
        if (warp == 15) {
            bar_sync<2, 160>();
            asm volatile("fence.release.gpu;" ::: "memory");
            if (lane == 0) stg_rlx32(gs->flag + cta * 32, tag.x | tag.y >> 11);
            TSX(16, lane == 0);
            __syncwarp();
        }
        TS(5);
        const uint4* rp = gs->ent + (cta * NCTA + warp * 2) * GPITCH;
        const uint4* hp = rp + (min(lane >> 1, 4) * 32 + (lane & 1)) * GPITCH;
        rp += half * GPITCH + (lane & 15);
        uint64_t en[10];
        uint32_t rk[20];
#pragma unroll
        for (int i = 0; i < 10; i++) en[i] = ja | (uint64_t)jb << 32;
        const uint32_t row0 = warp * 2 + half, cx = row0 * CHUNK - (tag.x >> 8), cy = row0 * CHUNK - (tag.y >> 8);
        const uint32_t ce[2] = {row0 * 2, min(row0 + 32, 40u) * 2};
        int nl = -1;
        bool fail = false;
        uint32_t pend = (1u << 2 * nr) - 1, todo = (1u << nr) - 1, got = 0;
        for (int it = 0;; it++) {
            const uint2 h = ldg_rlx64_if(hp, (pend >> lane) & 1);
            uint32_t next = 0;
#pragma unroll
            for (int k = 0; k < 5; k++) {
                if (got & (1u << k)) {
                    const uint32_t a = en[2 * k], b = en[2 * k] >> 32, c = en[2 * k + 1], d = en[2 * k + 1] >> 32;
                    if (__builtin_expect(__any_sync(0xffffffffu, ((a ^ tag.x) | (b ^ tag.y) | (c ^ tag.x) | (d ^ tag.y)) >= (1u << 21)), 0)) next |= 1u << k;
                    else {
                        rk[4 * k] = bin_slot(a);
                        rk[4 * k + 1] = bin_slot(b);
                        rk[4 * k + 2] = bin_slot(c);
                        rk[4 * k + 3] = bin_slot(d);
                    }
                }
            }
#pragma unroll
            for (int k = 0; k < 5; k++) {
                if (got & ~next & (1u << k)) {
                    const uint32_t cs = k * 32 * CHUNK + (k < 2 ? ce[k & 1] : 80);
                    uint32_t v[4];
#pragma unroll
                    for (int j = 0; j < 4; j++) {
                        const uint32_t e = en[2 * k + (j >> 1)] >> (j & 1) * 32;
                        v[j] = __funnelshift_r(e, e, 8) + (cs + (j & 1 ? cy : cx));
                        sts32_z(A_BIN + rk[4 * k + j], v[j], rk[4 * k + j] & ~0x1fffu);
                    }
                    en[2 * k] = v[0] | (uint64_t)v[1] << 32;
                    en[2 * k + 1] = v[2] | (uint64_t)v[3] << 32;
                }
            }
            uint32_t hd;
            asm volatile("{\n.reg .u32 t;\nshr.u32 t, %5, 5;\nlop3.b32 t, %1, %2, t, 0xbe;\nlop3.b32 %0, %3, %4, t, 0xbe;\n}" : "=r"(hd) : "r"(h.x), "r"(tag.x), "r"(h.y), "r"(tag.y), "r"(next));
            const bool ok = hd < (1u << 21) && ((pend >> lane) & 1);
            if (ok) nl = (h.x >> 8) & 0x1fff;
            if (ok && nl > CAP) { fail = true; nl = -1; }
            pend &= ~__ballot_sync(0xffffffffu, ok);
            uint32_t seen = 0;
#pragma unroll
            for (int k = 0; k < 5; k++) if (!(pend & (3u << 2 * k))) seen |= 1u << k;
            seen &= todo;
            todo &= ~seen;
            got = next | seen;
            if (!(got | todo)) break;
            if (it >= SPIN) { fail = true; nl = -1; break; }
            if (got) {
#pragma unroll
                for (int k = 0; k < 5; k++) ldg_rlx128_upd(en[2 * k], en[2 * k + 1], rp + k * 32 * GPITCH, (got & (1u << k)) && (lane & 15) * 4 <= __shfl_sync(0xffffffffu, nl, 2 * k + half));
            }
        }
        TW(2);
        uint32_t big = __ballot_sync(0xffffffffu, nl >= 64);
        while (__builtin_expect(big != 0, 0)) {
            const int k = __ffs(big) - 1;
            big &= big - 1;
            const int n = __shfl_sync(0xffffffffu, nl, k), row = (k >> 1) * 32 + warp * 2 + (k & 1);
            if (64 + 4 * lane <= n) {
                uint4 ex;
                bool bad = true;
                for (int it = 0; it < SPIN; it++) {
                    ex = ldg_rlx128_if(gs->ent + (cta * NCTA + row) * GPITCH + 16 + lane, true);
                    bad = ((ex.x ^ tag.x) | (ex.y ^ tag.y) | (ex.z ^ tag.x) | (ex.w ^ tag.y)) >= (1u << 21);
                    if (!bad) break;
                }
                if (bad) fail = true;
                else {
#pragma unroll
                    for (int j = 0; j < 4; j++) {
                        const uint32_t a = j == 0 ? ex.x : j == 1 ? ex.y : j == 2 ? ex.z : ex.w;
                        if (64 + 4 * lane + j <= n) {
                            const uint32_t v = (a << 24) + ((a >> 8) & 0x1fff) + chunk_start(row);
                            sts32(A_BIN + min(bin_slot(a), DUMP), v);
                        }
                    }
                }
            }
            __syncwarp();
        }
        TW(3);
        if (fail) sts32(A_MISC, 1);
        __syncwarp();
        if (lane == 0) mbar_arrive(bar_r);
        mbar_wait(bar_r, 0);
        TS(7);
        if (!fail) {
#pragma unroll
            for (int i = 0; i < 20; i++)
                if (i < 16 || nr == 5) sts32(A_BIN + min(rk[i], DUMP), en[i >> 1] >> (i & 1) * 32);
        }
        bar_arrive<5, NT>();
        TW(7);
        const uint32_t qb = A_QH + hh * QP + (lane & 7) * 128 + ((qch ^ (lane & 7)) << 4);
        uint32_t acc[2][16], h[16], q[4], s[4], tt[WP];
        ldsm4t(q, qb + (lane < 16 ? strm * ((nb - 1) & ~1) : strm * (nb - 2) | 1) * 1024);
#pragma unroll
        for (int i = 0; i < 4; i++) s[i] = 0;
#pragma unroll
        for (int i = 0; i < 5; i++) fence_regs(w[i]);
        fence_regs(q); fence_regs(s);
        uint32_t eva = A_EV + strm * 128, clk = 0;
        const int fd = strm ? 2048 : -2048;
        const uint32_t lox = ((A_XR >> 4) | 0x10000) + strm * 512, loe = ((A_ER >> 4) | 0x10000) + strm * 128, los = ((A_SEL >> 4) | 0x10000) + strm * 128;
        const uint32_t bar_full = A_BAR + strm * 8, bar_empty = bar_full + R * 8;
        auto gemm = [&](int st, uint32_t ph, uint32_t (&d)[16]) {
            mbar_wait(bar_full + st * 16, ph);
            wg_fence();
            mma64h0<HI128>(d, w[0], lox + st * 1024);
            mma64h<1, HI128>(d, w[1], lox + st * 1024 + 2);
            mma64h<1, HI128>(d, w[2], lox + st * 1024 + 4);
            mma64h<1, HI128>(d, w[3], lox + st * 1024 + 6);
            mma64h<1, HI32>(d, w[4], loe + st * 256);
            mma64h<1, HI32>(d, q, los + st * 256);
            wg_commit();
        };
        uint32_t ph = 0;
        gemm(0, 0, acc[0]);
        TS(11); TC(21);
        const Sched sc = schedule(lane, nb);
        if (!sc.fail) {
            if (strm ? lane >= sc.B0 && lane < nb - 2 : lane >= 2 && lane <= sc.B0) sts8(A_EV + strm * 128 - 1 + ((strm ? sc.total - sc.start - sc.len : sc.start) >> 6), lane + 32);
            if (lane == 0) { sts8(A_EV + strm * 128 + (strm ? sc.L1 : sc.L), 255); sts32(A_MISC + 4, sc.B0); }
        }
        __syncwarp();
        TW(6);
        wg_wait0();
        fence_regs(acc[0]);
        if (!sc.fail) {
        if (lane == 0) mbar_arrive(bar_empty);
#pragma unroll
        for (int i = 0; i < WP; i++) tt[i] = htanh2(acc[0][i]);
        for (;;) {
            TL(min(((eva - A_EV) >> 2) & 31, 15));
            const uint32_t evw = lds32(eva);
#pragma unroll
            for (int st = 0; st < 4; st++) {
                const uint32_t ev = (evw >> (8 * st)) & 255;
                if (__builtin_expect(ev != 0, 0)) {
                    if (ev == 255) goto finished;
                    const uint32_t qa = qb - 32 * 1024 + ev * 1024, fa = qa + fd;
                    if (ev & 1) { stsm2t(fa, s[2], s[3]); ldsm2t(q[2], q[3], qa); s[2] = 0; s[3] = 0; }
                    else { stsm2t(fa, s[0], s[1]); ldsm2t(q[0], q[1], qa); s[0] = 0; s[1] = 0; }
                    fence_regs(s); fence_regs(q);
                }
                uint32_t (&u)[16] = acc[st & 1];
                uint32_t (&v)[16] = acc[(st + 1) & 1];
                if (st == 3) ph ^= 1;
                gemm((st + 1) & 3, ph, v);
#pragma unroll
                for (int i = 0; i < 16; i++) {
                    if (i == SFP) { fence_regs(h); asm volatile("mov.u32 %0, %%clock;" : "=r"(clk)::"memory"); fence_regs(u); }
                    h[i] = hfma2(u[i], i < WP ? tt[i] : htanh2(u[i]), u[i]);
                }
                wg_fence();
#pragma unroll
                for (int k = 0; k < 4; k++) mma16t<HI32>(s, h[4 * k], h[4 * k + 1], h[4 * k + 2], h[4 * k + 3], los + st * 256 + k * 32);
                wg_commit();
                wg_wait1();
                fence_regs(v);
                if (lane == 0) mbar_arrive(bar_empty + ((st + 1) & 3) * 16);
#pragma unroll
                for (int i = 0; i < WP; i++) { tt[i] = htanh2(v[i]); asm volatile("" : "+r"(tt[i])::"memory"); }
                wg_wait0();
                fence_regs(s);
            }
            eva += 4;
        }
    finished:
        TS(12); TC(22);
        {
            const uint2 ms = lds64(A_MISC);
            const bool odd = ms.y & 1;
            const uint32_t l0 = odd ? s[2] : s[0], l1 = odd ? s[3] : s[1], a = qb + ms.y * 1024;
            stsm2t(a + fd / 2, odd ? s[0] : s[2], odd ? s[1] : s[3]);
            if (strm) stsm2t(qb + 24 * 1024, l0, l1);
            bar_sync<3, NT>();
            if (!strm) {
                uint32_t a0, a1;
                ldsm2t(a0, a1, qb + 24 * 1024);
                stsm2t(a, hadd2(l0, a0), hadd2(l1, a1));
            }
            bad = clk & ms.x;
        }
        proxy_fence();
        uint32_t a2[8][4];
        const uint32_t wa = A_W2 + (((lane >> 4) & 1) * 8 + (lane & 7)) * 144 + qch * 16;
#pragma unroll
        for (int i = 0; i < 8; i++) ldsm4t(a2[i], wa + i * 16 * 144);
        const float bo0 = __uint_as_float(lds16(A_B2 + (wq * 16 + (lane >> 2)) * 2) << 16);
        const float bo1 = __uint_as_float(lds16(A_B2 + (wq * 16 + 8 + (lane >> 2)) * 2) << 16);
        float d[24];
#pragma unroll
        for (int i = 0; i < 8; i++) fence_regs(a2[i]);
        bar_sync<6, 512>();
        TS(13);
        const uint32_t lo = ((A_QH >> 4) | 0x10000) + wg * 384;
        wg_fence();
        mma48f<0, HI128>(d, a2[0], lo);
#pragma unroll
        for (int i = 1; i < 8; i++) mma48f<1, HI128>(d, a2[i], lo + (i >> 2) * (QP / 16) + (i & 3) * 2);
        wg_commit();
        float dg[12];
#pragma unroll
        for (int j = 0; j < 6; j++) {
            const uint2 v = lds64(A_DEG + (wg * 48 + j * 8 + (lane & 3) * 2) * 4);
            dg[2 * j] = (float)v.x; dg[2 * j + 1] = (float)v.y;
        }
        wg_wait0();
        fence_regs(d);
        uint32_t r[12];
#pragma unroll
        for (int j = 0; j < 6; j++) {
            const float g0 = dg[2 * j], g1 = dg[2 * j + 1];
            const float v0 = g0 > 0.f ? fmaf(g0, bo0, d[4 * j]) : 0.f, v1 = g1 > 0.f ? fmaf(g1, bo0, d[4 * j + 1]) : 0.f;
            const float v2 = g0 > 0.f ? fmaf(g0, bo1, d[4 * j + 2]) : 0.f, v3 = g1 > 0.f ? fmaf(g1, bo1, d[4 * j + 3]) : 0.f;
            bad |= !(fabsf(v0) + fabsf(v1) + fabsf(v2) + fabsf(v3) < 3.0e38f);
            r[2 * j] = pack_b2(v0, v1); r[2 * j + 1] = pack_b2(v2, v3);
        }
        const uint32_t oa = A_OUT + (wg * 48 + (lane >> 4) * 8 + (lane & 7)) * 128 + ((qch ^ (lane & 7)) << 4);
#pragma unroll
        for (int j = 0; j < 3; j++) stsm4t(oa + j * 2048, r[4 * j], r[4 * j + 1], r[4 * j + 2], r[4 * j + 3]);
        asm volatile("bar.sync %0, 128;" ::"r"(7 + wg) : "memory");
#pragma unroll
        for (int j = 0; j < 3; j++) {
            const int row = wg * 48 + j * 16 + wq * 4 + (lane >> 3);
            const uint4 v = lds128(A_OUT + row * 128 + (((lane ^ row) & 7) << 4));
            if (row < nrows) ((uint4*)out)[(cta * NPC + row) * 8 + (lane & 7)] = v;
        }
        } else bad = 1;
    }
    TS(14);
    if (__syncthreads_or(bad)) slow_path(smem_raw, x, ea, src, dst, w1, b1, w2, b2, out);
}

}

extern "C" void kernel_launch(void* const* d_in, const int* in_sizes, int n_in, void* d_out, int out_size) {
    typedef CUresult (*EncodeFn)(CUtensorMap*, CUtensorMapDataType, cuuint32_t, void*, const cuuint64_t*, const cuuint64_t*, const cuuint32_t*,
                                 const cuuint32_t*, CUtensorMapInterleave, CUtensorMapSwizzle, CUtensorMapL2promotion, CUtensorMapFloatOOBfill);
    static bool init = false;
    static EncodeFn encode = nullptr;
    static void* scratch = nullptr;
    if (!init) {
        cudaFuncSetAttribute(mpnn_kernel, cudaFuncAttributeMaxDynamicSharedMemorySize, SMEM_BYTES);
        void* fn = nullptr;
        cudaDriverEntryPointQueryResult st;
        if (cudaGetDriverEntryPoint("cuTensorMapEncodeTiled", &fn, cudaEnableDefault, &st) == cudaSuccess && st == cudaDriverEntryPointSuccess) encode = (EncodeFn)fn;
        if (cudaGetSymbolAddress(&scratch, g_scratch) != cudaSuccess) scratch = nullptr;
        init = true;
    }
    CUtensorMap map = {};
    const cuuint64_t dims[2] = {128, 144}, strides[1] = {256};
    const cuuint32_t box[2] = {64, 16}, estr[2] = {1, 1};
    const bool have_map = encode && encode(&map, CU_TENSOR_MAP_DATA_TYPE_BFLOAT16, 2, d_in[4], dims, strides, box, estr, CU_TENSOR_MAP_INTERLEAVE_NONE,
                                          CU_TENSOR_MAP_SWIZZLE_128B, CU_TENSOR_MAP_L2_PROMOTION_NONE, CU_TENSOR_MAP_FLOAT_OOB_FILL_NONE) == CUDA_SUCCESS;
    mpnn_kernel<<<NCTA, NT, SMEM_BYTES>>>((const __nv_bfloat16*)d_in[0], (const __nv_bfloat16*)d_in[1], (const int*)d_in[2], (const int*)d_in[3],
                                          (const __nv_bfloat16*)d_in[4], (const __nv_bfloat16*)d_in[5], (const __nv_bfloat16*)d_in[6],
                                          (const __nv_bfloat16*)d_in[7], (__nv_bfloat16*)d_out, have_map ? (Scratch*)scratch : nullptr, map);
}
```

```cpp
#include <cuda_runtime.h>
#include <cuda.h>
#include <cuda_bf16.h>
#include <cuda_fp16.h>
#include <stdint.h>

namespace {

constexpr int N_NODES = 25000;
constexpr int N_EDGES = 800000;
constexpr int NCTA = 132;
constexpr int NPC = 190;
constexpr int NT = 640;
constexpr int NP = 512;
constexpr int CHUNK = 6060;
constexpr int R = 8;
#define GF
#define SFP 3
#define FSL 100
#define FPOS 0
#define WP 1
constexpr int CB = 352;
constexpr int MINB = 128;
constexpr int CAP = 91;
constexpr int SPITCH = 368;
constexpr int GPITCH = 24;
constexpr uint32_t TAGMOD = (1u << 22) - 1;
constexpr uint32_t EMPTY = 0xff000000u;
constexpr int SPIN = 1 << 16;
#define MBSPIN (1 << 22)

constexpr uint32_t SB = 1024;
constexpr uint32_t A_XR = SB;
constexpr uint32_t A_ER = A_XR + R * 8192;
constexpr uint32_t A_SEL = A_ER + R * 2048;
constexpr uint32_t QP = 200 * 128;
constexpr uint32_t A_QH = A_SEL + R * 2048;
constexpr uint32_t A_BIN = A_QH + 2 * QP;
constexpr uint32_t BIN1 = 0xa00, DUMP = BIN1 + 23 * CB * 4;
constexpr uint32_t A_CNT = A_BIN + DUMP + 16;
constexpr uint32_t A_BC = A_CNT + 136 * 4;
constexpr uint32_t A_DEG = A_BC + 32 * 4;
constexpr uint32_t A_EV = A_DEG + 256 * 4;
constexpr uint32_t A_MISC = A_EV + 256;
constexpr uint32_t A_ZEND = A_MISC + 16;
constexpr uint32_t A_TAG = A_ZEND;
constexpr uint32_t A_B1 = A_TAG + 16;
constexpr uint32_t A_B2 = A_B1 + 256;
constexpr uint32_t A_BAR = A_B2 + 128;
constexpr uint32_t A_SS = A_BAR + 20 * 8;
constexpr uint32_t A_END = A_SS + 4 * 512;
constexpr int SMEM_BYTES = A_END - SB;
constexpr uint32_t A_STG = A_XR;
constexpr uint32_t A_WB = A_SEL;
constexpr uint32_t A_WA = A_XR + 49 * 1024;
constexpr uint32_t A_XO = A_QH + QP;
constexpr uint32_t A_W2 = A_BIN;
constexpr uint32_t A_OUT = A_XR;
static_assert(A_STG + (NCTA + 1) * SPITCH + 16 <= A_WA && A_WA + 2 * 10240 <= A_SEL && CB * 4 + 1024 <= BIN1 && BIN1 + 3 * CB * 4 <= 0x2000 && DUMP % 16 == 0 && 24 * CB / 128 < 128, "alias");
static_assert(A_W2 % 1024 == 0 && A_QH % 1024 == 0 && QP % 1024 == 0 && A_WA % 1024 == 0 && A_SEL % 1024 == 0, "align");
static_assert(A_CNT % 16 == 0 && A_ZEND % 16 == 0 && A_B2 % 16 == 0 && A_B1 % 16 == 0 && A_BAR % 8 == 0 && A_BC % 16 == 0 && A_DEG % 8 == 0 && A_MISC % 16 == 0 && A_SS % 16 == 0, "align");
static_assert(SMEM_BYTES <= 199680 && A_ZEND - A_CNT <= 2048, "smem");

struct Scratch {
    uint32_t flag[NCTA * 32];
    uint32_t cnt, pad[31];
    uint4 x16[N_NODES * 8];
    uint4 ent[NCTA * NCTA * GPITCH];
};
__device__ __align__(128) Scratch g_scratch;

#define TL(i)
#define TI(it, v)
#define TC(i)
#define TV(i, v)
#define TS(i)
#define TW(i)
#define TWD(i, v)
#define TSX(i, cond)

__device__ __forceinline__ void wg_fence() { asm volatile("wgmma.fence.sync.aligned;" ::: "memory"); }
__device__ __forceinline__ void wg_commit() { asm volatile("wgmma.commit_group.sync.aligned;" ::: "memory"); }
__device__ __forceinline__ void wg_wait0() { asm volatile("wgmma.wait_group.sync.aligned 0;" ::: "memory"); }
__device__ __forceinline__ void wg_wait1() { asm volatile("wgmma.wait_group.sync.aligned 1;" ::: "memory"); }
template <int M> __device__ __forceinline__ void fence_regs(uint32_t (&d)[M]) {
#pragma unroll
    for (int i = 0; i < M; i++) asm volatile("" : "+r"(d[i])::"memory");
}
template <int M> __device__ __forceinline__ void fence_regs(float (&d)[M]) {
#pragma unroll
    for (int i = 0; i < M; i++) asm volatile("" : "+f"(d[i])::"memory");
}
constexpr uint32_t HI128 = 0x40000040;
constexpr uint32_t HI32 = 0xC0000010;
template <int SC, uint32_t HI>
__device__ __forceinline__ void mma64h(uint32_t (&d)[16], const uint32_t (&a)[4], uint32_t lo) {
    asm volatile("{\n.reg .pred p;\n.reg .b64 dsc;\nsetp.ne.b32 p, %21, 0;\nmov.b64 dsc, {%20, %22};\n"
        "wgmma.mma_async.sync.aligned.m64n64k16.f16.f16.f16 {%0, %1, %2, %3, %4, %5, %6, %7, %8, %9, %10, %11, %12, %13, %14, %15}, {%16, %17, %18, %19}, dsc, p, 1, 1, 0;\n}\n"
        : "+r"(d[0]), "+r"(d[1]), "+r"(d[2]), "+r"(d[3]), "+r"(d[4]), "+r"(d[5]), "+r"(d[6]), "+r"(d[7]), "+r"(d[8]), "+r"(d[9]), "+r"(d[10]), "+r"(d[11]), "+r"(d[12]), "+r"(d[13]), "+r"(d[14]), "+r"(d[15])
        : "r"(a[0]), "r"(a[1]), "r"(a[2]), "r"(a[3]), "r"(lo), "n"(SC), "n"(HI));
}
template <uint32_t HI>
__device__ __forceinline__ void mma64h0(uint32_t (&d)[16], const uint32_t (&a)[4], uint32_t lo) {
    asm volatile("{\n.reg .pred p;\n.reg .b64 dsc;\nsetp.ne.b32 p, 0, 0;\nmov.b64 dsc, {%20, %21};\n"
        "wgmma.mma_async.sync.aligned.m64n64k16.f16.f16.f16 {%0, %1, %2, %3, %4, %5, %6, %7, %8, %9, %10, %11, %12, %13, %14, %15}, {%16, %17, %18, %19}, dsc, p, 1, 1, 0;\n}\n"
        : "=r"(d[0]), "=r"(d[1]), "=r"(d[2]), "=r"(d[3]), "=r"(d[4]), "=r"(d[5]), "=r"(d[6]), "=r"(d[7]), "=r"(d[8]), "=r"(d[9]), "=r"(d[10]), "=r"(d[11]), "=r"(d[12]), "=r"(d[13]), "=r"(d[14]), "=r"(d[15])
        : "r"(a[0]), "r"(a[1]), "r"(a[2]), "r"(a[3]), "r"(lo), "n"(HI));
}
template <uint32_t HI>
__device__ __forceinline__ void mma16t(uint32_t (&d)[4], uint32_t a0, uint32_t a1, uint32_t a2, uint32_t a3, uint32_t lo) {
    asm volatile("{\n.reg .pred p;\n.reg .b64 dsc;\nsetp.eq.b32 p, 0, 0;\nmov.b64 dsc, {%8, %9};\n"
        "wgmma.mma_async.sync.aligned.m64n16k16.f16.f16.f16 {%0, %1, %2, %3}, {%4, %5, %6, %7}, dsc, p, 1, 1, 1;\n}\n"
        : "+r"(d[0]), "+r"(d[1]), "+r"(d[2]), "+r"(d[3]) : "r"(a0), "r"(a1), "r"(a2), "r"(a3), "r"(lo), "n"(HI));
}
template <int SC, uint32_t HI>
__device__ __forceinline__ void mma96h(uint32_t (&d)[24], const uint32_t (&a)[4], uint32_t lo) {
    asm volatile("{\n.reg .pred p;\n.reg .b64 dsc;\nsetp.ne.b32 p, %29, 0;\nmov.b64 dsc, {%28, %30};\n"
        "wgmma.mma_async.sync.aligned.m64n96k16.f16.f16.f16 {%0, %1, %2, %3, %4, %5, %6, %7, %8, %9, %10, %11, %12, %13, %14, %15, %16, %17, %18, %19, %20, %21, %22, %23}, {%24, %25, %26, %27}, dsc, p, 1, 1, 0;\n}\n"
        : "+r"(d[0]), "+r"(d[1]), "+r"(d[2]), "+r"(d[3]), "+r"(d[4]), "+r"(d[5]), "+r"(d[6]), "+r"(d[7]), "+r"(d[8]), "+r"(d[9]), "+r"(d[10]), "+r"(d[11]), "+r"(d[12]), "+r"(d[13]), "+r"(d[14]), "+r"(d[15]), "+r"(d[16]), "+r"(d[17]), "+r"(d[18]), "+r"(d[19]), "+r"(d[20]), "+r"(d[21]), "+r"(d[22]), "+r"(d[23])
        : "r"(a[0]), "r"(a[1]), "r"(a[2]), "r"(a[3]), "r"(lo), "n"(SC), "n"(HI));
}
template <int SC>
__device__ __forceinline__ void mma48f(float (&d)[24], uint32_t la, uint32_t lb) {
    asm volatile("{\n.reg .pred p;\n.reg .b64 da, db;\nsetp.ne.b32 p, %26, 0;\nmov.b64 da, {%24, %27};\nmov.b64 db, {%25, %27};\n"
        "wgmma.mma_async.sync.aligned.m64n48k16.f32.f16.f16 {%0, %1, %2, %3, %4, %5, %6, %7, %8, %9, %10, %11, %12, %13, %14, %15, %16, %17, %18, %19, %20, %21, %22, %23}, da, db, p, 1, 1, 1, 0;\n}\n"
        : "+f"(d[0]), "+f"(d[1]), "+f"(d[2]), "+f"(d[3]), "+f"(d[4]), "+f"(d[5]), "+f"(d[6]), "+f"(d[7]), "+f"(d[8]), "+f"(d[9]), "+f"(d[10]), "+f"(d[11]), "+f"(d[12]), "+f"(d[13]), "+f"(d[14]), "+f"(d[15]), "+f"(d[16]), "+f"(d[17]), "+f"(d[18]), "+f"(d[19]), "+f"(d[20]), "+f"(d[21]), "+f"(d[22]), "+f"(d[23])
        : "r"(la), "r"(lb), "n"(SC), "n"(HI128));
}
template <int SC>
__device__ __forceinline__ void mma8f(float (&d)[4], uint32_t la, uint32_t lb) {
    asm volatile("{\n.reg .pred p;\n.reg .b64 da, db;\nsetp.ne.b32 p, %6, 0;\nmov.b64 da, {%4, %7};\nmov.b64 db, {%5, %7};\n"
        "wgmma.mma_async.sync.aligned.m64n8k16.f32.f16.f16 {%0, %1, %2, %3}, da, db, p, 1, 1, 1, 0;\n}\n"
        : "+f"(d[0]), "+f"(d[1]), "+f"(d[2]), "+f"(d[3]) : "r"(la), "r"(lb), "n"(SC), "n"(HI128));
}
__device__ __forceinline__ uint32_t hadd2(uint32_t a, uint32_t b) { uint32_t r; asm("add.rn.f16x2 %0, %1, %2;" : "=r"(r) : "r"(a), "r"(b)); return r; }
__device__ __forceinline__ uint32_t hfma2(uint32_t a, uint32_t b, uint32_t c) { uint32_t r; asm("fma.rn.f16x2 %0, %1, %2, %3;" : "=r"(r) : "r"(a), "r"(b), "r"(c)); return r; }
__device__ __forceinline__ uint32_t bfma2(uint32_t a, uint32_t b, uint32_t c) { uint32_t r; asm("fma.rn.bf16x2 %0, %1, %2, %3;" : "=r"(r) : "r"(a), "r"(b), "r"(c)); return r; }
__device__ __forceinline__ uint32_t htanh2(uint32_t a) { uint32_t r; asm("tanh.approx.f16x2 %0, %1;" : "=r"(r) : "r"(a)); return r; }
__device__ __forceinline__ uint32_t pack_h2(float lo, float hi) { uint32_t r; asm("cvt.rn.f16x2.f32 %0, %1, %2;" : "=r"(r) : "f"(hi), "f"(lo)); return r; }
__device__ __forceinline__ uint32_t pack_b2(float lo, float hi) { uint32_t r; asm("cvt.rn.bf16x2.f32 %0, %1, %2;" : "=r"(r) : "f"(hi), "f"(lo)); return r; }
__device__ __forceinline__ uint32_t bf2h(uint32_t v) { return pack_h2(__uint_as_float(v << 16), __uint_as_float(v & 0xffff0000u)); }
__device__ __forceinline__ uint32_t bf2h_half(uint32_t v) { return pack_h2(0.5f * __uint_as_float(v << 16), 0.5f * __uint_as_float(v & 0xffff0000u)); }
__device__ __forceinline__ uint4 bf2h4(uint4 v) { return make_uint4(bf2h(v.x), bf2h(v.y), bf2h(v.z), bf2h(v.w)); }

__device__ __forceinline__ void cp16(uint32_t s, const void* g) { asm volatile("cp.async.cg.shared.global [%0], [%1], 16;" ::"r"(s), "l"(g) : "memory"); }
__device__ __forceinline__ void cp_commit() { asm volatile("cp.async.commit_group;" ::: "memory"); }
template <int N> __device__ __forceinline__ void cp_wait() { asm volatile("cp.async.wait_group %0;" ::"n"(N) : "memory"); }
__device__ __forceinline__ void bulk_g2s(uint32_t s, const void* g, uint32_t bytes, uint32_t bar) {
    asm volatile("cp.async.bulk.shared::cluster.global.mbarrier::complete_tx::bytes [%0], [%1], %2, [%3];" ::"r"(s), "l"(g), "r"(bytes), "r"(bar) : "memory");
}
__device__ __forceinline__ void tma_g2s(uint32_t s, const CUtensorMap* m, int c0, int c1, uint32_t bar) {
    asm volatile("cp.async.bulk.tensor.2d.shared::cluster.global.mbarrier::complete_tx::bytes [%0], [%1, {%2, %3}], [%4];" ::"r"(s), "l"(m), "r"(c0), "r"(c1), "r"(bar) : "memory");
}
__device__ __forceinline__ void l2_prefetch(const void* g, uint32_t bytes) { asm volatile("cp.async.bulk.prefetch.L2.global [%0], %1;" ::"l"(g), "r"(bytes) : "memory"); }
__device__ __forceinline__ void proxy_fence() { asm volatile("fence.proxy.async.shared::cta;" ::: "memory"); }
__device__ __forceinline__ bool mbar_try(uint32_t bar, uint32_t parity) {
    uint32_t ok;
    asm volatile("{\n.reg .pred p;\nmbarrier.try_wait.parity.shared::cta.b64 p, [%1], %2;\nselp.u32 %0, 1, 0, p;\n}" : "=r"(ok) : "r"(bar), "r"(parity) : "memory");
    return ok;
}
__device__ __forceinline__ bool mbar_test(uint32_t bar, uint32_t parity) {
    uint32_t ok;
    asm volatile("{\n.reg .pred p;\nmbarrier.test_wait.parity.shared::cta.b64 p, [%1], %2;\nselp.u32 %0, 1, 0, p;\n}" : "=r"(ok) : "r"(bar), "r"(parity) : "memory");
    return ok;
}
__device__ __forceinline__ void mbar_wait(uint32_t bar, uint32_t parity) {
    if (__builtin_expect(!mbar_try(bar, parity), 0))
        for (int it = 0; it < MBSPIN; it++) if (mbar_try(bar, parity)) break;
}
__device__ __forceinline__ void mbar_arrive(uint32_t bar) { asm volatile("mbarrier.arrive.shared::cta.b64 _, [%0];" ::"r"(bar) : "memory"); }
__device__ __forceinline__ uint32_t lds32(uint32_t a) { uint32_t r; asm volatile("ld.shared.u32 %0, [%1];" : "=r"(r) : "r"(a) : "memory"); return r; }
__device__ __forceinline__ uint32_t lds32_rlx(uint32_t a) { uint32_t r; asm volatile("ld.relaxed.cta.shared.u32 %0, [%1];" : "=r"(r) : "r"(a) : "memory"); return r; }
__device__ __forceinline__ uint32_t lds16(uint32_t a) { uint32_t r; asm volatile("ld.shared.u16 %0, [%1];" : "=r"(r) : "r"(a) : "memory"); return r; }
__device__ __forceinline__ uint2 lds64(uint32_t a) { uint2 r; asm volatile("ld.shared.v2.u32 {%0,%1}, [%2];" : "=r"(r.x), "=r"(r.y) : "r"(a) : "memory"); return r; }
__device__ __forceinline__ uint4 lds128(uint32_t a) { uint4 r; asm volatile("ld.shared.v4.u32 {%0,%1,%2,%3}, [%4];" : "=r"(r.x), "=r"(r.y), "=r"(r.z), "=r"(r.w) : "r"(a) : "memory"); return r; }
__device__ __forceinline__ void sts128(uint32_t a, uint4 v) { asm volatile("st.shared.v4.u32 [%0], {%1,%2,%3,%4};" ::"r"(a), "r"(v.x), "r"(v.y), "r"(v.z), "r"(v.w) : "memory"); }
__device__ __forceinline__ void sts64(uint32_t a, uint32_t x, uint32_t y) { asm volatile("st.shared.v2.u32 [%0], {%1,%2};" ::"r"(a), "r"(x), "r"(y) : "memory"); }
__device__ __forceinline__ void sts32(uint32_t a, uint32_t v) { asm volatile("st.shared.u32 [%0], %1;" ::"r"(a), "r"(v) : "memory"); }
__device__ __forceinline__ void sts16(uint32_t a, uint32_t v) { asm volatile("st.shared.u16 [%0], %1;" ::"r"(a), "r"(v) : "memory"); }
__device__ __forceinline__ void sts8(uint32_t a, uint32_t v) { asm volatile("st.shared.u8 [%0], %1;" ::"r"(a), "r"(v) : "memory"); }
__device__ __forceinline__ void sts32_z(uint32_t a, uint32_t v, uint32_t z) {
    asm volatile("{\n.reg .pred p;\nsetp.eq.u32 p, %2, 0;\n@p st.relaxed.cta.shared.u32 [%0], %1;\n}" ::"r"(a), "r"(v), "r"(z) : "memory");
}
__device__ __forceinline__ uint32_t atoms_inc(uint32_t a) { uint32_t r; asm volatile("atom.shared.add.u32 %0, [%1], 1;" : "=r"(r) : "r"(a) : "memory"); return r; }
__device__ __forceinline__ uint32_t bin_slot(uint32_t e) {
    uint32_t r;
    asm volatile("atom.shared.add.u32 %0, [%1], 4;" : "=r"(r) : "r"(A_BC + ((e >> 1) & 0x7c)) : "memory");
    return r;
}
__device__ __forceinline__ uint32_t bin_base(int b, int nb) { return b == 0 ? 0u : BIN1 + (b == nb - 1 ? 0 : b == 1 ? 1 : b == nb - 2 ? 2 : b + 1) * CB * 4; }
__device__ __forceinline__ void deg_inc(uint32_t v) { asm volatile("red.shared.add.u32 [%0], 1;" ::"r"(A_DEG + (v >> 22)) : "memory"); }
__device__ __forceinline__ uint32_t ldg_rlx32(const void* p) { uint32_t r; asm volatile("ld.relaxed.gpu.global.u32 %0, [%1];" : "=r"(r) : "l"(p) : "memory"); return r; }
#define LDI "ld.relaxed.gpu.global.v2.u32"
__device__ __forceinline__ int2 ldg64(const void* p) { int2 r; asm volatile(LDI " {%0,%1}, [%2];" : "=r"(r.x), "=r"(r.y) : "l"(p) : "memory"); return r; }
__device__ __forceinline__ void ldg64_if(int2& r, const void* p, bool on) {
    asm volatile("{\n.reg .pred p;\nsetp.ne.u32 p, %3, 0;\n@p " LDI " {%0,%1}, [%2];\n}" : "+r"(r.x), "+r"(r.y) : "l"(p), "r"((uint32_t)on) : "memory");
}
__device__ __forceinline__ uint4 ldg_rlx128_if(const void* p, bool on) {
    uint4 r;
    asm volatile("{\n.reg .pred p;\n.reg .b64 a, b;\nsetp.ne.u32 p, %5, 0;\n@p ld.relaxed.gpu.global.v2.b64 {a, b}, [%4];\nmov.b64 {%0,%1}, a;\nmov.b64 {%2,%3}, b;\n}"
                 : "=r"(r.x), "=r"(r.y), "=r"(r.z), "=r"(r.w) : "l"(p), "r"((uint32_t)on) : "memory");
    return r;
}
__device__ __forceinline__ void ldg_rlx128_upd(uint64_t& a, uint64_t& b, const void* p, bool on) {
    asm volatile("{\n.reg .pred p;\nsetp.ne.u32 p, %3, 0;\n@p ld.relaxed.gpu.global.v2.b64 {%0, %1}, [%2];\n}" : "+l"(a), "+l"(b) : "l"(p), "r"((uint32_t)on) : "memory");
}
__device__ __forceinline__ uint2 ldg_rlx64_if(const void* p, bool on) {
    uint64_t a = 0;
    asm volatile("{\n.reg .pred p;\nsetp.ne.u32 p, %2, 0;\n@p ld.relaxed.gpu.global.b64 %0, [%1];\n}" : "+l"(a) : "l"(p), "r"((uint32_t)on) : "memory");
    return make_uint2((uint32_t)a, (uint32_t)(a >> 32));
}
__device__ __forceinline__ uint4 ldg_acq128(const void* p) {
    uint4 r;
    asm volatile("ld.acquire.gpu.global.v4.u32 {%0,%1,%2,%3}, [%4];" : "=r"(r.x), "=r"(r.y), "=r"(r.z), "=r"(r.w) : "l"(p) : "memory");
    return r;
}
__device__ __forceinline__ void stg_rlx32(void* p, uint32_t v) { asm volatile("st.relaxed.gpu.global.u32 [%0], %1;" ::"l"(p), "r"(v) : "memory"); }
__device__ __forceinline__ void stg_rlx128(void* p, uint4 v) {
    asm volatile("{\n.reg .b64 a, b;\nmov.b64 a, {%1,%2};\nmov.b64 b, {%3,%4};\nst.relaxed.gpu.global.v2.b64 [%0], {a, b};\n}" ::"l"(p), "r"(v.x), "r"(v.y), "r"(v.z), "r"(v.w) : "memory");
}
__device__ __forceinline__ void stg_rlx128_if(void* p, uint4 v, bool on) {
    asm volatile("{\n.reg .pred p;\n.reg .b64 a, b;\nsetp.ne.u32 p, %5, 0;\nmov.b64 a, {%1,%2};\nmov.b64 b, {%3,%4};\n@p st.relaxed.gpu.global.v2.b64 [%0], {a, b};\n}" ::"l"(p), "r"(v.x), "r"(v.y), "r"(v.z), "r"(v.w), "r"((uint32_t)on) : "memory");
}
__device__ __forceinline__ void ldsm4t(uint32_t (&r)[4], uint32_t a) {
    asm volatile("ldmatrix.sync.aligned.m8n8.x4.trans.shared.b16 {%0,%1,%2,%3}, [%4];" : "=r"(r[0]), "=r"(r[1]), "=r"(r[2]), "=r"(r[3]) : "r"(a) : "memory");
}
__device__ __forceinline__ void ldsm2t(uint32_t& r0, uint32_t& r1, uint32_t a) {
    asm volatile("ldmatrix.sync.aligned.m8n8.x2.trans.shared.b16 {%0,%1}, [%2];" : "=r"(r0), "=r"(r1) : "r"(a) : "memory");
}
__device__ __forceinline__ void stsm2t(uint32_t a, uint32_t r0, uint32_t r1) {
    asm volatile("stmatrix.sync.aligned.m8n8.x2.trans.shared.b16 [%0], {%1,%2};" ::"r"(a), "r"(r0), "r"(r1) : "memory");
}
__device__ __forceinline__ void stsm4t(uint32_t a, uint32_t r0, uint32_t r1, uint32_t r2, uint32_t r3) {
    asm volatile("stmatrix.sync.aligned.m8n8.x4.trans.shared.b16 [%0], {%1,%2,%3,%4};" ::"r"(a), "r"(r0), "r"(r1), "r"(r2), "r"(r3) : "memory");
}
template <int ID, int N> __device__ __forceinline__ void bar_sync() { asm volatile("bar.sync %0, %1;" ::"n"(ID), "n"(N) : "memory"); }
template <int ID, int N> __device__ __forceinline__ void bar_arrive() { asm volatile("bar.arrive %0, %1;" ::"n"(ID), "n"(N) : "memory"); }
__device__ __forceinline__ uint32_t scan_up(uint32_t v) {
#pragma unroll
    for (int o = 1; o < 32; o <<= 1)
        asm volatile("{\n.reg .pred p;\n.reg .u32 t;\nshfl.sync.up.b32 t|p, %0, %1, 0, -1;\n@p add.u32 %0, %0, t;\n}" : "+r"(v) : "r"(o));
    return v;
}
__device__ __forceinline__ float bf2f(const __nv_bfloat16* p) { return __bfloat162float(*p); }

__device__ __forceinline__ int chunk_start(int c) { return c * CHUNK + min(c, 40) * 2; }
static_assert(NCTA * CHUNK + 80 == N_EDGES && CHUNK / 2 + 1 <= 6 * NP && CHUNK / 2 >= 5 * NP, "chunks");

struct Sched { uint32_t len, start, total; int L, L1, B0; bool fail; };
__device__ __forceinline__ Sched schedule(int lane, int nb) {
    Sched r;
    const uint32_t n = (lds32(A_BC + lane * 4) - bin_base(lane, nb)) >> 2, f = lds32(A_MISC);
    r.len = lane < nb ? max(n, (uint32_t)MINB) : 0u;
    const uint32_t end = scan_up(r.len);
    r.start = end - r.len;
    r.total = __shfl_sync(0xffffffffu, end, 31);
    r.L = (r.total + 127) >> 7;
    r.L1 = ((r.total + 63) >> 6) - r.L;
    r.B0 = __popc(__ballot_sync(0xffffffffu, end <= 64u * r.L));
    r.fail = __any_sync(0xffffffffu, r.len > CB || f);
    return r;
}
static_assert(64 * ((14 * MINB + 127) / 128) >= 2 * CB && 14 * MINB / 2 - 64 > 2 * CB && 14 * MINB / 2 - 64 - CB >= 7 * 64, "block B0 is never among the first two of a stream");

__device__ __noinline__ void slow_path(uint8_t* sp, const __nv_bfloat16* x, const __nv_bfloat16* ea, const int* src, const int* dst,
                                       const __nv_bfloat16* w1, const __nv_bfloat16* b1, const __nv_bfloat16* w2,
                                       const __nv_bfloat16* b2, __nv_bfloat16* out) {
    const int tid = threadIdx.x, lane = tid & 31, warp = tid >> 5, cta = blockIdx.x;
    const int nrows = min(NPC, N_NODES - cta * NPC);
    float* hs = (float*)sp;
    __nv_bfloat16* w1s = (__nv_bfloat16*)(sp + 192 * 128 * 4);
    int* dg = (int*)(sp + 192 * 128 * 4 + 144 * 128 * 2);
    __syncthreads();
    for (int i = tid; i < 192 * 128; i += NT) hs[i] = 0.f;
    for (int i = tid; i < 144 * 128; i += NT) w1s[i] = w1[i];
    for (int i = tid; i < 192; i += NT) dg[i] = 0;
    __syncthreads();
    float bb[4];
    for (int j = 0; j < 4; j++) bb[j] = bf2f(b1 + lane * 4 + j);
    for (int i0 = warp * 32; i0 < N_EDGES; i0 += NT) {
        const int mine = dst[i0 + lane] - cta * NPC;
        uint32_t hit = __ballot_sync(0xffffffffu, (unsigned)mine < (unsigned)nrows);
        while (hit) {
            const int b = __ffs(hit) - 1;
            hit &= hit - 1;
            const int eid = i0 + b, dl = __shfl_sync(0xffffffffu, mine, b), s = src[eid];
            float v[5];
            v[0] = bf2f(x + s * 64 + lane); v[1] = bf2f(x + s * 64 + 32 + lane);
            v[2] = bf2f(x + (cta * NPC + dl) * 64 + lane); v[3] = bf2f(x + (cta * NPC + dl) * 64 + 32 + lane);
            v[4] = lane < 16 ? bf2f(ea + (size_t)eid * 16 + lane) : 0.f;
            float z[4] = {bb[0], bb[1], bb[2], bb[3]};
#pragma unroll
            for (int c = 0; c < 5; c++) {
                for (int kk = 0; kk < (c == 4 ? 16 : 32); kk++) {
                    float a = __shfl_sync(0xffffffffu, v[c], kk);
                    const __nv_bfloat16* wr = w1s + (c * 32 + kk) * 128 + lane * 4;
#pragma unroll
                    for (int j = 0; j < 4; j++) z[j] = fmaf(a, __bfloat162float(wr[j]), z[j]);
                }
            }
#pragma unroll
            for (int j = 0; j < 4; j++) atomicAdd(&hs[dl * 128 + lane * 4 + j], z[j] / (1.f + expf(-z[j])));
            if (lane == 0) atomicAdd(&dg[dl], 1);
        }
    }
    __syncthreads();
    for (int i = tid; i < nrows * 64; i += NT) {
        int n = i >> 6, d = i & 63;
        float a = 0.f;
        if (dg[n] > 0) {
            a = (float)dg[n] * bf2f(b2 + d);
            for (int h = 0; h < 128; h++) a = fmaf(hs[n * 128 + h], bf2f(w2 + h * 64 + d), a);
        }
        out[(size_t)(cta * NPC + n) * 64 + d] = __float2bfloat16(a);
    }
}

__global__ void __launch_bounds__(NT, 1)
mpnn_kernel(const __nv_bfloat16* __restrict__ x, const __nv_bfloat16* __restrict__ ea, const int* __restrict__ src,
            const int* __restrict__ dst, const __nv_bfloat16* __restrict__ w1, const __nv_bfloat16* __restrict__ b1,
            const __nv_bfloat16* __restrict__ w2, const __nv_bfloat16* __restrict__ b2, __nv_bfloat16* __restrict__ out,
            Scratch* __restrict__ gs, const __grid_constant__ CUtensorMap w1map) {
    extern __shared__ uint8_t smem_raw[];
    const int tid = threadIdx.x, lane = tid & 31;
    __builtin_assume(tid < NT);
    const int warp = __shfl_sync(0xffffffffu, tid >> 5, 0);
    const int cta = blockIdx.x;
    const int nrows = min(NPC, N_NODES - cta * NPC), nb = (nrows + 7) >> 3;
    const int e0 = chunk_start(cta);
    const int nv2 = CHUNK / 2 + (cta < 40);
    if ((uint32_t)__cvta_generic_to_shared(smem_raw) != SB || !gs) { slow_path(smem_raw, x, ea, src, dst, w1, b1, w2, b2, out); return; }
    constexpr uint32_t bar_w = A_BAR + R * 16, bar_x = bar_w + 8, bar_r = bar_x + 8;
    const int wg = warp >> 2, wq = warp & 3, hh = wg & 1, strm = wg >> 1;
    const uint32_t qch = wq * 2 + ((lane >> 3) & 1);
    const uint32_t wofs = (((lane >> 4) & 1) * 8 + (lane & 7)) * 128 + ((qch ^ (lane & 7)) << 4);
    int bad = 0;
    TS(0);

    int2 d2[6];
    const int pt = tid - NP;
    if (wg == 4) {
        uint32_t cnt0;
        if (pt == 64) cnt0 = ldg_rlx32(&gs->cnt);
        if (pt == 96) {
#pragma unroll
            for (int i = 0; i < 2 * R + 3; i++) asm volatile("mbarrier.init.shared::cta.b64 [%0], %1;" ::"r"(A_BAR + i * 8), "r"(i < R ? 2 : i < 2 * R ? 8 : i < 2 * R + 2 ? 1 : NT / 32) : "memory");
            proxy_fence();
            asm volatile("mbarrier.arrive.expect_tx.shared::cta.b64 _, [%0], %1;" ::"r"(bar_w), "r"(144 * 256 + 256 + 128) : "memory");
            asm volatile("mbarrier.arrive.expect_tx.shared::cta.b64 _, [%0], %1;" ::"r"(bar_x), "r"(nrows * 128) : "memory");
        }
        __syncwarp();
        stg_rlx128_if((uint4*)gs->flag + cta * 8 + (lane & 1), make_uint4(0, 0, 0, 0), pt < 2);
        if (pt < (int)(A_ZEND - A_CNT) / 16) sts128(A_CNT + pt * 16, make_uint4(0, 0, 0, 0));
        if (pt == 64) {
            const uint32_t tag = cnt0 / NCTA + 1;
            sts64(A_TAG, tag << 21, tag >> 11 << 21);
        }
    } else {
        const int2* dp = (const int2*)(dst + e0) + tid;
        d2[5] = make_int2(NCTA * NPC, NCTA * NPC);
#pragma unroll
        for (int r = 0; r < 5; r++) d2[r] = ldg64(dp + r * NP);
        ldg64_if(d2[5], dp + 5 * NP, tid < nv2 - 5 * NP);
        stg_rlx128_if(gs->ent + ((tid >> 1) * NCTA + cta) * GPITCH + (lane & 1), make_uint4(0, 0, 0, 0), tid < 2 * NCTA);
    }
    __syncthreads();
    const uint2 tag = lds64(A_TAG);
    if (wg == 4) {
        const uint32_t tagw = tag.x | tag.y >> 11;
        if (warp == 19) {
            if (lane == 0) {
                bulk_g2s(A_XO, x + cta * NPC * 64, nrows * 128, bar_x);
                asm volatile("red.relaxed.gpu.global.inc.u32 [%0], %1;" ::"l"(&gs->cnt), "r"(NCTA * TAGMOD - 1) : "memory");
            }
            TSX(15, lane == 0);
            __syncwarp();
            if (lane < 18) {
                int i = lane + cta % 18;
                i = i >= 18 ? i - 18 : i;
                const int h = i & 1, rb = i >> 1;
                tma_g2s(rb >= 4 && rb < 8 ? A_WB + h * 8192 + (rb - 4) * 2048 : A_WA + h * 10240 + min(rb, 4) * 2048, &w1map, h * 64, rb * 16, bar_w);
            } else if (lane < 20) bulk_g2s(lane == 18 ? A_B1 : A_B2, lane == 18 ? b1 : b2, lane == 18 ? 256 : 128, bar_w);
            else if (lane == 20) l2_prefetch(w2, 128 * 64 * 2);
            __syncwarp();
        }
        if (warp == 16) sts32(A_BC + lane * 4, lane < 24 ? bin_base(lane, nb) : DUMP);
#pragma unroll 1
        for (uint32_t a = A_BIN + pt * 16; a < A_BIN + DUMP; a += 2048) sts128(a, make_uint4(EMPTY, EMPTY, EMPTY, EMPTY));
        bar_arrive<1, NT>();
        mbar_wait(bar_x, 0);
        TW(0);
        const uint32_t xo = A_XO + (pt >> 3) * 128 + (((pt ^ (pt >> 3)) & 7) << 4);
        {
            uint4 xr[12];
#pragma unroll
            for (int r = 0; r < 12; r++) xr[r] = lds128(A_XO + (r * 128 + pt) * 16);
            __syncwarp();
#pragma unroll
            for (int r = 0; r < 12; r++) {
                const bool in = r * 128 + pt < nrows * 8;
                const uint4 v = in ? bf2h4(xr[r]) : make_uint4(0, 0, 0, 0);
                sts128(xo + r * 2048, v);
                if (in) gs->x16[cta * NPC * 8 + r * 128 + pt] = v;
            }
        }
        bar_arrive<2, 160>();
        proxy_fence();
        mbar_wait(bar_w, 0);
        bar_sync<4, 128>();
        TW(1);
#pragma unroll 1
        for (int h = 0; h < 2; h++) {
            uint32_t wb[4][4], acc[2][24];
#pragma unroll
            for (int i = 0; i < 4; i++) ldsm4t(wb[i], A_WB + h * 8192 + wofs + i * 2048);
            const uint32_t bl0 = lds16(A_B1 + (h * 64 + wq * 16 + (lane >> 2)) * 2), bl1 = lds16(A_B1 + (h * 64 + wq * 16 + 8 + (lane >> 2)) * 2);
#pragma unroll
            for (int i = 0; i < 4; i++)
#pragma unroll
                for (int j = 0; j < 4; j++) wb[i][j] = bf2h_half(wb[i][j]);
            const uint32_t bq0 = bf2h_half(bl0 * 0x10001u), bq1 = bf2h_half(bl1 * 0x10001u);
#pragma unroll
            for (int i = 0; i < 4; i++) fence_regs(wb[i]);
            wg_fence();
#pragma unroll
            for (int n = 0; n < 2; n++) {
                const uint32_t lo = ((A_XO >> 4) | 0x10000) + n * 768;
                mma96h<0, HI128>(acc[n], wb[0], lo);
                mma96h<1, HI128>(acc[n], wb[1], lo + 2);
                mma96h<1, HI128>(acc[n], wb[2], lo + 4);
                mma96h<1, HI128>(acc[n], wb[3], lo + 6);
            }
            wg_commit();
            wg_wait0();
            fence_regs(acc[0]); fence_regs(acc[1]);
            if (h) {
                bar_sync<4, 128>();
            }
#pragma unroll
            for (int n = 0; n < 2; n++)
#pragma unroll
                for (int j = 0; j < 6; j++)
                    stsm4t(A_QH + h * QP + n * 12288 + wofs + j * 2048, hadd2(acc[n][4 * j], bq0), hadd2(acc[n][4 * j + 1], bq1), hadd2(acc[n][4 * j + 2], bq0), hadd2(acc[n][4 * j + 3], bq1));
        }
        if (pt == 64) l2_prefetch(src + cta * 6064, min(6064, N_EDGES - cta * 6064) * 4);
        TW(2);
        const int par = wq >> 1, hf = wq & 1, gq = lane >> 3, cp = (lane >> 1) & 3;
        const uint32_t sel = A_SEL + hf * 2048 + (par * 32 + lane) * 32 + ((lane >> 2) & 1) * 16;
#pragma unroll
        for (int r = 0; r < 8; r++) sts128(A_SEL + hf * 2048 + par * 1024 + (r >> 1) * 4096 + (r & 1) * 512 + lane * 16, make_uint4(0, 0, 0, 0));
        const uint32_t bar_full = A_BAR + hf * 8, bar_empty = bar_full + R * 8;
        uint32_t xd[8];
#pragma unroll
        for (int c = 0; c < 8; c++) xd[c] = A_XR + hf * 8192 + (par * 32 + gq * 8) * 128 + (((lane & 7) ^ c) << 4);
        fence_regs(xd);
        uint32_t ed0 = A_ER + hf * 2048 + (par * 32 + gq * 8 + cp) * 32 + (lane & 1) * 16, ed1 = (ed0 ^ 16) + 128;
        const uint32_t sw = A_SS + wq * 128 + lane * 4, sr = A_SS + wq * 128 + gq * 32;
        const char* xg = (const char*)gs->x16 + (lane & 7) * 16;
        const char* eg = (const char*)ea + (lane & 1) * 16;
        const char* sp = (const char*)src;
        int bi = hf ? nb - 1 : 0;
        uint32_t ta = A_BIN + hf * BIN1 + (par * 32 + lane) * 4;
        asm volatile("" : "+l"(xg), "+l"(eg), "+l"(sp), "+r"(ed0), "+r"(ed1), "+r"(ta));
        uint32_t prev[4] = {sel, sel, sel, sel}, own[4], col[4];
        auto issue_e = [&](int st, uint32_t e) {
            const uint32_t e0 = __shfl_sync(0xffffffffu, e, gq * 8 + cp), e1 = __shfl_sync(0xffffffffu, e, gq * 8 + cp + 4);
            cp16(ed0 + st * 4096, eg + (size_t)(e0 & 0xfffff) * 32);
            cp16(ed1 + st * 4096, eg + (size_t)(e1 & 0xfffff) * 32);
            col[st] = e;
        };
        auto issue_x = [&](int st, const uint4& a0, const uint4& a1) {
            const uint32_t a[8] = {a0.x, a0.y, a0.z, a0.w, a1.x, a1.y, a1.z, a1.w};
#pragma unroll
            for (int i = 0; i < 8; i++) cp16(xd[i] + st * 16384 + i * 128, xg + (size_t)a[i] * 128);
        };
        auto fetch_src = [&](int slot, uint32_t e) {
            asm volatile("cp.async.ca.shared.global [%0], [%1], 4;" ::"r"(sw + slot * 512), "l"(sp + (size_t)(e & 0xfffff) * 4) : "memory");
        };
        auto finish = [&](int u) {
            const uint4 v0 = lds128(ed0 + u * 4096), v1 = lds128(ed1 + u * 4096);
            sts16(prev[u] + u * 4096, 0);
            prev[u] = sel ^ ((col[u] >> 23) & 0x1e);
            sts16(prev[u] + u * 4096, col[u] < (192u << 24) ? 0x3c00 : 0);
            deg_inc(col[u]);
            sts128(ed0 + u * 4096, bf2h4(v0));
            sts128(ed1 + u * 4096, bf2h4(v1));
            proxy_fence();
            __syncwarp();
            if (lane == 0) mbar_arrive(bar_full + u * 16);
        };
        __syncwarp();
        if (lane == 0) mbar_arrive(bar_r);
        auto flags = [&]() {
            const uint32_t* fp = gs->flag + (wq * 33 + lane) * 32;
#pragma unroll 1
            for (int it = 0;; it++) {
                const uint32_t f0 = ldg_rlx32(fp), f1 = ldg_rlx32(gs->flag + (wq * 33 + 32) * 32);
                if (__all_sync(0xffffffffu, f0 == tagw && f1 == tagw)) break;
                if (it >= SPIN) { bad = 1; break; }
                __nanosleep(FSL);
            }
            asm volatile("fence.acquire.gpu;" ::: "memory");
            TSX(17, tid == 512);
        };
        bar_sync<12, NT>();
        TW(7);
#pragma unroll 1
        for (int it = 0; it < MBSPIN; it++) {
            const bool all = mbar_test(bar_r, 0);
            col[0] = lds32_rlx(ta);
            col[1] = lds32_rlx(ta + 256);
            if (__all_sync(0xffffffffu, all || (col[0] != EMPTY && col[1] != EMPTY))) break;
            __nanosleep(40);
        }
        {
            const uint32_t ea = ta + (gq * 8 + cp - lane) * 4;
            const uint32_t a0 = lds32_rlx(ea), a1 = lds32_rlx(ea + 16), a2 = lds32_rlx(ea + 256), a3 = lds32_rlx(ea + 256 + 16);
            fetch_src(0, col[0]);
            fetch_src(1, col[1]);
            cp_commit();
            TWD(0, col[1]);
            cp16(ed0, eg + (size_t)(a0 & 0xfffff) * 32);
            cp16(ed1, eg + (size_t)(a1 & 0xfffff) * 32);
            cp16(ed0 + 4096, eg + (size_t)(a2 & 0xfffff) * 32);
            cp16(ed1 + 4096, eg + (size_t)(a3 & 0xfffff) * 32);
            cp_commit();
            ta += 256;
        }
        flags();
        cp_wait<1>();
        bar_sync<4, 128>();
        TWD(2, ta);
        issue_x(0, lds128(sr), lds128(sr + 16));
        cp_commit();
        issue_x(1, lds128(sr + 512), lds128(sr + 512 + 16));
        cp_commit();
        TW(4);
        mbar_wait(bar_r, 0);
        TSX(9, tid == 512);
        uint32_t bs = A_BIN + bin_base(lane, nb), be = max(A_BIN + lds32(A_BC + lane * 4), bs + MINB * 4);
        const int dir = hf ? -1 : 1;
        uint32_t nx = __shfl_sync(0xffffffffu, be, bi);
        auto next_entry = [&]() {
            ta += 256;
            while (__builtin_expect(__any_sync(0xffffffffu, ta >= nx), 0)) {
                const bool c = ta >= nx;
                if (c) bi += dir;
                const uint32_t s2 = __shfl_sync(0xffffffffu, bs, bi), e2 = __shfl_sync(0xffffffffu, be, bi);
                if (c) { ta += s2 - nx; nx = e2; }
            }
            return lds32(ta);
        };
        own[2] = next_entry();
        own[3] = next_entry();
        fetch_src(2, own[2]);
        fetch_src(3, own[3]);
        cp_commit();
        issue_e(2, own[2]);
        issue_e(3, own[3]);
        cp_commit();
        TW(1);
        cp_wait<3>();
        TW(5);
        finish(0);
        cp_wait<2>();
        finish(1);
        TW(6);
        bar_sync<5, NT>();
        TW(3);
        own[0] = next_entry();
        own[1] = next_entry();
        fetch_src(0, own[0]);
        fetch_src(1, own[1]);
        cp_commit();
        own[2] = next_entry();
        cp_wait<2>();
        __syncwarp();
        issue_x(2, lds128(sr + 1024), lds128(sr + 1024 + 16));
        cp_commit();
        issue_x(3, lds128(sr + 1536), lds128(sr + 1536 + 16));
        fetch_src(2, own[2]);
        cp_commit();
        const Sched sc = schedule(lane, nb);
        if (!sc.fail) {
            const int L = hf ? sc.L1 : sc.L;
            if (lane == sc.B0) { const uint32_t cut = bs + (64 * sc.L - sc.start) * 4; if (hf) bs = cut; else be = cut; }
            if (lane == sc.B0 + dir) { bs = A_BIN + CB * 4; be = ~0u; }
            cp_wait<2>();
            __syncwarp();
            uint32_t ph = 1;
            for (int j = L;; j -= 4) {
#pragma unroll
                for (int u = 2; u < 6; u++) {
                    if (j == u) goto done;
                    if (u == 2) ph ^= 1;
                    const int st = (u + 2) & 3;
                    if (j > u + 2) {
                        const uint32_t es = next_entry();
                        const uint4 a0 = lds128(sr + st * 512), a1 = lds128(sr + st * 512 + 16);
                        fetch_src((st + 3) & 3, es);
                        mbar_wait(bar_empty + st * 16, ph);
                        issue_e(st, own[st]);
                        issue_x(st, a0, a1);
                        own[(st + 3) & 3] = es;
                    } else mbar_wait(bar_empty + st * 16, ph);
                    cp_commit();
                    cp_wait<2>();
                    finish(u & 3);
                }
            }
        done:
            if (lane == 0) mbar_arrive(bar_full + (L & 3) * 16);
            TSX(18, tid == 512);
            uint4 v[8];
#pragma unroll
            for (int i = 0; i < 8; i++) v[i] = __ldg((const uint4*)w2 + i * 128 + pt);
            bar_sync<4, 128>();
#pragma unroll
            for (int i = 0; i < 8; i++) sts128(A_W2 - A_XO + xo + i * 2048, bf2h4(v[i]));
            proxy_fence();
            bar_arrive<3, NT>();
        } else bad = 1;
        cp_wait<0>();
    } else {
        TS(1);
        const uint32_t jn = 192 + (lane & 3) * 8 + (lane & 16) * 2, ja = tag.x + jn, jb = tag.y + jn;
        const int nr = warp < NCTA / 2 - 64 ? 5 : 4, half = lane >> 4;
        {
            uint32_t c[12], rk[12];
#pragma unroll
            for (int i = 0; i < 12; i++) {
                c[i] = __umulhi(i & 1 ? d2[i >> 1].y : d2[i >> 1].x, 44151u << 9);
                rk[i] = atoms_inc(A_CNT + c[i] * 4);
            }
            TS(2);
            const uint32_t tb = tag.y + (tid << 9), td = tag.x - tag.y;
#pragma unroll
            for (int i = 0; i < 12; i++)
                sts32(A_STG + 4 + c[i] * SPITCH + min(rk[i], (uint32_t)CAP) * 4,
                      (i & 1 ? d2[i >> 1].y : d2[i >> 1].x) + tb + (((i >> 1) * NP * 2 + (i & 1)) << 8) - c[i] * NPC + (rk[i] & 1) * td);
        }
        bar_sync<1, NT>();
        TS(3);
        {
            const uint32_t row = warp * 2 + half, p0 = (lane & 15) * 4;
            uint4* gp = gs->ent + (row * NCTA + cta) * GPITCH + (lane & 15);
            const uint32_t sp = A_STG + row * SPITCH + (lane & 15) * 16;
            uint32_t n[5];
            uint4 v[5];
#pragma unroll
            for (int k = 0; k < 5; k++) {
                n[k] = lds32(A_CNT + min(row + k * 32, NCTA + 1) * 4);
                v[k] = lds128(sp + k * 32 * SPITCH);
            }
            uint32_t big = 0;
#pragma unroll
            for (int k = 0; k < 5; k++) {
                if (p0 - 1 >= n[k]) v[k].x = p0 ? ja : ja + (n[k] << 8);
                if (p0 + 1 > n[k]) v[k].y = jb;
                if (p0 + 2 > n[k]) v[k].z = ja;
                if (p0 + 3 > n[k]) v[k].w = jb;
                stg_rlx128_if(gp + k * 32 * NCTA * GPITCH, v[k], (p0 & ~7u) <= n[k] && (k < 4 || nr == 5));
                if (n[k] >= 64 && (k < 4 || nr == 5)) big |= 1u << k;
            }
            while (__builtin_expect(big != 0, 0)) {
                const int k = __ffs(big) - 1;
                big &= big - 1;
                const uint32_t m = lds32(A_CNT + (row + k * 32) * 4), p = p0 + 64;
                if (p0 < 32 && (p & ~7u) <= m) {
                    uint4 u = lds128(sp + k * 32 * SPITCH + 256);
                    if (p > m) u.x = ja;
                    if (p + 1 > m) u.y = jb;
                    if (p + 2 > m) u.z = ja;
                    if (p + 3 > m) u.w = jb;
                    stg_rlx128(gp + k * 32 * NCTA * GPITCH + 16, u);
                }
            }
            __syncwarp();
        }
        TS(4); TW(0);
        uint32_t w[5][4];
        auto load_w = [&]() {
            mbar_wait(bar_w, 0);
#pragma unroll
            for (int i = 0; i < 5; i++) ldsm4t(w[i], A_WA + hh * 10240 + wofs + i * 2048);
#pragma unroll
            for (int i = 0; i < 5; i++) {
#pragma unroll
                for (int j = 0; j < 4; j++) w[i][j] = bf2h_half(w[i][j]);
                fence_regs(w[i]);
            }
        };
        load_w();
        bar_arrive<12, NT>();
        if (warp == 15) {
            bar_sync<2, 160>();
            asm volatile("fence.release.gpu;" ::: "memory");
            if (lane == 0) stg_rlx32(gs->flag + cta * 32, tag.x | tag.y >> 11);
            TSX(16, lane == 0);
            __syncwarp();
        }
        TS(5);
        const uint4* rp = gs->ent + (cta * NCTA + warp * 2) * GPITCH;
        const uint4* hp = rp + (min(lane >> 1, 4) * 32 + (lane & 1)) * GPITCH;
        rp += half * GPITCH + (lane & 15);
        uint64_t en[10];
        uint32_t rk[20];
#pragma unroll
        for (int i = 0; i < 10; i++) en[i] = ja | (uint64_t)jb << 32;
        const uint32_t row0 = warp * 2 + half, cx = row0 * CHUNK - (tag.x >> 8), cy = row0 * CHUNK - (tag.y >> 8);
        const uint32_t ce[2] = {row0 * 2, min(row0 + 32, 40u) * 2};
        int nl = -1;
        bool fail = false;
        uint32_t pend = (1u << 2 * nr) - 1, todo = (1u << nr) - 1, got = 0;
        for (int it = 0;; it++) {
            const uint2 h = ldg_rlx64_if(hp, (pend >> lane) & 1);
            uint32_t next = 0;
#pragma unroll
            for (int k = 0; k < 5; k++) {
                if (got & (1u << k)) {
                    const uint32_t a = en[2 * k], b = en[2 * k] >> 32, c = en[2 * k + 1], d = en[2 * k + 1] >> 32;
                    if (__builtin_expect(__any_sync(0xffffffffu, ((a ^ tag.x) | (b ^ tag.y) | (c ^ tag.x) | (d ^ tag.y)) >= (1u << 21)), 0)) next |= 1u << k;
                    else {
                        rk[4 * k] = bin_slot(a);
                        rk[4 * k + 1] = bin_slot(b);
                        rk[4 * k + 2] = bin_slot(c);
                        rk[4 * k + 3] = bin_slot(d);
                    }
                }
            }
#pragma unroll
            for (int k = 0; k < 5; k++) {
                if (got & ~next & (1u << k)) {
                    const uint32_t cs = k * 32 * CHUNK + (k < 2 ? ce[k & 1] : 80);
                    uint32_t v[4];
#pragma unroll
                    for (int j = 0; j < 4; j++) {
                        const uint32_t e = en[2 * k + (j >> 1)] >> (j & 1) * 32;
                        v[j] = __funnelshift_r(e, e, 8) + (cs + (j & 1 ? cy : cx));
                        sts32_z(A_BIN + rk[4 * k + j], v[j], rk[4 * k + j] & ~0x1fffu);
                    }
                    en[2 * k] = v[0] | (uint64_t)v[1] << 32;
                    en[2 * k + 1] = v[2] | (uint64_t)v[3] << 32;
                }
            }
            uint32_t hd;
            asm volatile("{\n.reg .u32 t;\nshr.u32 t, %5, 5;\nlop3.b32 t, %1, %2, t, 0xbe;\nlop3.b32 %0, %3, %4, t, 0xbe;\n}" : "=r"(hd) : "r"(h.x), "r"(tag.x), "r"(h.y), "r"(tag.y), "r"(next));
            const bool ok = hd < (1u << 21) && ((pend >> lane) & 1);
            if (ok) nl = (h.x >> 8) & 0x1fff;
            if (ok && nl > CAP) { fail = true; nl = -1; }
            pend &= ~__ballot_sync(0xffffffffu, ok);
            uint32_t seen = 0;
#pragma unroll
            for (int k = 0; k < 5; k++) if (!(pend & (3u << 2 * k))) seen |= 1u << k;
            seen &= todo;
            todo &= ~seen;
            got = next | seen;
            TI(it, pend | got << 16 | next << 24);
            if (!(got | todo)) break;
            if (it >= SPIN) { fail = true; nl = -1; break; }
            if (got) {
#pragma unroll
                for (int k = 0; k < 5; k++) ldg_rlx128_upd(en[2 * k], en[2 * k + 1], rp + k * 32 * GPITCH, (got & (1u << k)) && (lane & 15) * 4 <= __shfl_sync(0xffffffffu, nl, 2 * k + half));
            }
            uint32_t big = __ballot_sync(0xffffffffu, ok && nl >= 64);
            while (__builtin_expect(big != 0, 0)) {
                uint32_t m = big;
#pragma unroll
                for (int g = 0; g < 4; g++) { if (g < lane >> 3) m &= m - 1; big &= big - 1; }
                const int k = __ffs(m) - 1, n = __shfl_sync(0xffffffffu, nl, k), row = (k >> 1) * 32 + warp * 2 + (k & 1), p = 64 + 4 * (lane & 7);
                if (m && p <= n) {
                    uint4 ex;
                    bool bad = true;
                    for (int it = 0; it < SPIN; it++) {
                        ex = ldg_rlx128_if(gs->ent + (cta * NCTA + row) * GPITCH + p / 4, true);
                        bad = ((ex.x ^ tag.x) | (ex.y ^ tag.y) | (ex.z ^ tag.x) | (ex.w ^ tag.y)) >= (1u << 21);
                        if (!bad) break;
                    }
                    if (bad) fail = true;
                    else {
#pragma unroll
                        for (int j = 0; j < 4; j++) {
                            const uint32_t a = j == 0 ? ex.x : j == 1 ? ex.y : j == 2 ? ex.z : ex.w;
                            if (p + j <= n) sts32_z(A_BIN + min(bin_slot(a), DUMP), (a << 24) + ((a >> 8) & 0x1fff) + chunk_start(row), 0);
                        }
                    }
                }
                __syncwarp();
            }
        }
        TW(2);
        TW(3);
        if (fail) sts32(A_MISC, 1);
        __syncwarp();
        if (lane == 0) mbar_arrive(bar_r);
        mbar_wait(bar_r, 0);
        TS(7);
        if (!fail) {
#pragma unroll
            for (int i = 0; i < 20; i++)
                if (i < 16 || nr == 5) sts32(A_BIN + min(rk[i], DUMP), en[i >> 1] >> (i & 1) * 32);
        }
        bar_arrive<5, NT>();
        TW(7);
        const uint32_t qb = A_QH + hh * QP + (lane & 7) * 128 + ((qch ^ (lane & 7)) << 4);
        uint32_t acc[2][16], h[16], q[4], s[4], tt[WP];
        ldsm4t(q, qb + (lane < 16 ? strm * ((nb - 1) & ~1) : strm * (nb - 2) | 1) * 1024);
#pragma unroll
        for (int i = 0; i < 4; i++) s[i] = 0;
#pragma unroll
        for (int i = 0; i < 5; i++) fence_regs(w[i]);
        fence_regs(q); fence_regs(s);
        uint32_t eva = A_EV + strm * 128, clk = 0;
        const int fd = strm ? 2048 : -2048;
        const uint32_t lox = ((A_XR >> 4) | 0x10000) + strm * 512, loe = ((A_ER >> 4) | 0x10000) + strm * 128, los = ((A_SEL >> 4) | 0x10000) + strm * 128;
        const uint32_t bar_full = A_BAR + strm * 8, bar_empty = bar_full + R * 8;
        auto gemm = [&](int st, uint32_t ph, uint32_t (&d)[16]) {
            mbar_wait(bar_full + st * 16, ph);
            wg_fence();
            mma64h0<HI128>(d, w[0], lox + st * 1024);
            mma64h<1, HI128>(d, w[1], lox + st * 1024 + 2);
            mma64h<1, HI128>(d, w[2], lox + st * 1024 + 4);
            mma64h<1, HI128>(d, w[3], lox + st * 1024 + 6);
            mma64h<1, HI32>(d, w[4], loe + st * 256);
            mma64h<1, HI32>(d, q, los + st * 256);
            wg_commit();
        };
        uint32_t ph = 0;
        gemm(0, 0, acc[0]);
        TS(11); TC(21);
        const Sched sc = schedule(lane, nb);
        if (!sc.fail) {
            if (strm ? lane >= sc.B0 && lane < nb - 2 : lane >= 2 && lane <= sc.B0) sts8(A_EV + strm * 128 - 1 + ((strm ? sc.total - sc.start - sc.len : sc.start) >> 6), lane + 32);
            if (lane == 0) { sts8(A_EV + strm * 128 + (strm ? sc.L1 : sc.L), 255); sts32(A_MISC + 4, sc.B0); }
        }
        __syncwarp();
        TW(6);
        wg_wait0();
        fence_regs(acc[0]);
        if (!sc.fail) {
        if (lane == 0) mbar_arrive(bar_empty);
#pragma unroll
        for (int i = 0; i < WP; i++) tt[i] = htanh2(acc[0][i]);
        for (;;) {
            TL(min(((eva - A_EV) >> 2) & 31, 15));
            const uint32_t evw = lds32(eva);
#pragma unroll
            for (int st = 0; st < 4; st++) {
                const uint32_t ev = (evw >> (8 * st)) & 255;
                if (__builtin_expect(ev != 0, 0)) {
                    if (ev == 255) goto finished;
                    const uint32_t qa = qb - 32 * 1024 + ev * 1024, fa = qa + fd;
                    if (ev & 1) { stsm2t(fa, s[2], s[3]); ldsm2t(q[2], q[3], qa); s[2] = 0; s[3] = 0; }
                    else { stsm2t(fa, s[0], s[1]); ldsm2t(q[0], q[1], qa); s[0] = 0; s[1] = 0; }
                    fence_regs(s); fence_regs(q);
                }
                uint32_t (&u)[16] = acc[st & 1];
                uint32_t (&v)[16] = acc[(st + 1) & 1];
                if (st == 3) ph ^= 1;
                gemm((st + 1) & 3, ph, v);
#pragma unroll
                for (int i = 0; i < 16; i++) {
                    if (i == SFP) { fence_regs(h); asm volatile("mov.u32 %0, %%clock;" : "=r"(clk)::"memory"); fence_regs(u); }
                    h[i] = hfma2(u[i], i < WP ? tt[i] : htanh2(u[i]), u[i]);
                }
                wg_fence();
#pragma unroll
                for (int k = 0; k < 4; k++) mma16t<HI32>(s, h[4 * k], h[4 * k + 1], h[4 * k + 2], h[4 * k + 3], los + st * 256 + k * 32);
                wg_commit();
                wg_wait1();
                fence_regs(v);
                if (lane == 0) mbar_arrive(bar_empty + ((st + 1) & 3) * 16);
#pragma unroll
                for (int i = 0; i < WP; i++) { tt[i] = htanh2(v[i]); asm volatile("" : "+r"(tt[i])::"memory"); }
                wg_wait0();
                fence_regs(s);
            }
            eva += 4;
        }
    finished:
        TS(12); TC(22);
        const uint2 ms = lds64(A_MISC);
        {
            const bool odd = ms.y & 1;
            const uint32_t a = qb + ms.y * 1024;
            stsm2t(a + fd / 2, odd ? s[0] : s[2], odd ? s[1] : s[3]);
            stsm2t(strm ? qb + 24 * 1024 : a, odd ? s[2] : s[0], odd ? s[3] : s[1]);
            bad = clk & ms.x;
        }
        proxy_fence();
        const float bo0 = __uint_as_float(lds16(A_B2 + (wq * 16 + (lane >> 2)) * 2) << 16);
        const float bo1 = __uint_as_float(lds16(A_B2 + (wq * 16 + 8 + (lane >> 2)) * 2) << 16);
        float d[24], d1[4];
        const int j0 = ms.y - wg * 6;
        bar_sync<3, NT>();
        TS(13);
        constexpr uint32_t la = (A_W2 >> 4) | 0x10000, lq = (A_QH >> 4) | 0x10000;
        wg_fence();
        mma48f<0>(d, la, lq + wg * 384);
#pragma unroll
        for (int i = 1; i < 8; i++) mma48f<1>(d, la + i * 128, lq + wg * 384 + (i >> 2) * (QP / 16) + (i & 3) * 2);
        wg_commit();
        if ((unsigned)j0 < 6) {
            wg_fence();
            mma8f<0>(d1, la, lq + 24 * 64);
#pragma unroll
            for (int i = 1; i < 8; i++) mma8f<1>(d1, la + i * 128, lq + 24 * 64 + (i >> 2) * (QP / 16) + (i & 3) * 2);
            wg_commit();
        }
        float dg[12];
#pragma unroll
        for (int j = 0; j < 6; j++) {
            const uint2 v = lds64(A_DEG + (wg * 48 + j * 8 + (lane & 3) * 2) * 4);
            dg[2 * j] = (float)v.x; dg[2 * j + 1] = (float)v.y;
        }
        fence_regs(dg);
        wg_wait0();
        fence_regs(d); fence_regs(d1);
        uint32_t r[12], nf = 0;
#pragma unroll
        for (int j = 0; j < 6; j++) {
            if (j == j0) { d[4 * j] += d1[0]; d[4 * j + 1] += d1[1]; d[4 * j + 2] += d1[2]; d[4 * j + 3] += d1[3]; }
            r[2 * j] = pack_b2(fmaf(dg[2 * j], bo0, d[4 * j]), fmaf(dg[2 * j + 1], bo0, d[4 * j + 1]));
            r[2 * j + 1] = pack_b2(fmaf(dg[2 * j], bo1, d[4 * j + 2]), fmaf(dg[2 * j + 1], bo1, d[4 * j + 3]));
            nf = bfma2(r[2 * j], 0, bfma2(r[2 * j + 1], 0, nf));
        }
        bad |= nf & 0x7fff7fff;
        const uint32_t oa = A_OUT + (wg * 48 + (lane >> 4) * 8 + (lane & 7)) * 128 + ((qch ^ (lane & 7)) << 4);
#pragma unroll
        for (int j = 0; j < 3; j++) stsm4t(oa + j * 2048, r[4 * j], r[4 * j + 1], r[4 * j + 2], r[4 * j + 3]);
        asm volatile("bar.sync %0, 128;" ::"r"(7 + wg) : "memory");
#pragma unroll
        for (int j = 0; j < 3; j++) {
            const int row = wg * 48 + j * 16 + wq * 4 + (lane >> 3);
            const uint4 v = lds128(A_OUT + row * 128 + (((lane ^ row) & 7) << 4));
            if (row < nrows) ((uint4*)out)[(cta * NPC + row) * 8 + (lane & 7)] = v;
        }
        } else bad = 1;
    }
    TS(14);
    if (__syncthreads_or(bad)) slow_path(smem_raw, x, ea, src, dst, w1, b1, w2, b2, out);
}

}

extern "C" void kernel_launch(void* const* d_in, const int* in_sizes, int n_in, void* d_out, int out_size) {
    typedef CUresult (*EncodeFn)(CUtensorMap*, CUtensorMapDataType, cuuint32_t, void*, const cuuint64_t*, const cuuint64_t*, const cuuint32_t*,
                                 const cuuint32_t*, CUtensorMapInterleave, CUtensorMapSwizzle, CUtensorMapL2promotion, CUtensorMapFloatOOBfill);
    static bool init = false;
    static EncodeFn encode = nullptr;
    static void* scratch = nullptr;
    if (!init) {
        cudaFuncSetAttribute(mpnn_kernel, cudaFuncAttributeMaxDynamicSharedMemorySize, SMEM_BYTES);
        void* fn = nullptr;
        cudaDriverEntryPointQueryResult st;
        if (cudaGetDriverEntryPoint("cuTensorMapEncodeTiled", &fn, cudaEnableDefault, &st) == cudaSuccess && st == cudaDriverEntryPointSuccess) encode = (EncodeFn)fn;
        if (cudaGetSymbolAddress(&scratch, g_scratch) != cudaSuccess) scratch = nullptr;
        init = true;
    }
    CUtensorMap map = {};
    const cuuint64_t dims[2] = {128, 144}, strides[1] = {256};
    const cuuint32_t box[2] = {64, 16}, estr[2] = {1, 1};
    const bool have_map = encode && encode(&map, CU_TENSOR_MAP_DATA_TYPE_BFLOAT16, 2, d_in[4], dims, strides, box, estr, CU_TENSOR_MAP_INTERLEAVE_NONE,
                                          CU_TENSOR_MAP_SWIZZLE_128B, CU_TENSOR_MAP_L2_PROMOTION_NONE, CU_TENSOR_MAP_FLOAT_OOB_FILL_NONE) == CUDA_SUCCESS;
    mpnn_kernel<<<NCTA, NT, SMEM_BYTES>>>((const __nv_bfloat16*)d_in[0], (const __nv_bfloat16*)d_in[1], (const int*)d_in[2], (const int*)d_in[3],
                                          (const __nv_bfloat16*)d_in[4], (const __nv_bfloat16*)d_in[5], (const __nv_bfloat16*)d_in[6],
                                          (const __nv_bfloat16*)d_in[7], (__nv_bfloat16*)d_out, have_map ? (Scratch*)scratch : nullptr, map);
}
```

```cpp
#include <cuda_runtime.h>
#include <cuda.h>
#include <cuda_bf16.h>
#include <cuda_fp16.h>
#include <stdint.h>

namespace {

constexpr int N_NODES = 25000;
constexpr int N_EDGES = 800000;
constexpr int NCTA = 132;
constexpr int NPC = 190;
constexpr int NT = 640;
constexpr int NP = 512;
constexpr int CHUNK = 6060;
constexpr int R = 8;
constexpr int CB = 352;
constexpr int MINB = 128;
constexpr int CAP = 91;
constexpr int SPITCH = 368;
constexpr int GPITCH = 24;
constexpr uint32_t TAGMOD = (1u << 22) - 1;
constexpr uint32_t EMPTY = 0xff000000u;
constexpr int SPIN = 1 << 16;
#define MBSPIN (1 << 22)

constexpr uint32_t SB = 1024;
constexpr uint32_t A_XR = SB;
constexpr uint32_t A_ER = A_XR + R * 8192;
constexpr uint32_t A_SEL = A_ER + R * 2048;
constexpr uint32_t QP = 200 * 128;
constexpr uint32_t A_QH = A_SEL + R * 2048;
constexpr uint32_t A_BIN = A_QH + 2 * QP;
constexpr uint32_t BIN1 = 0xa00, DUMP = BIN1 + 23 * CB * 4;
constexpr uint32_t A_CNT = A_BIN + DUMP + 16;
constexpr uint32_t A_BC = A_CNT + 136 * 4;
constexpr uint32_t A_DEG = A_BC + 32 * 4;
constexpr uint32_t A_EV = A_DEG + 256 * 4;
constexpr uint32_t A_MISC = A_EV + 256;
constexpr uint32_t A_ZEND = A_MISC + 16;
constexpr uint32_t A_TAG = A_ZEND;
constexpr uint32_t A_B1 = A_TAG + 16;
constexpr uint32_t A_B2 = A_B1 + 256;
constexpr uint32_t A_BAR = A_B2 + 128;
constexpr uint32_t A_SS = A_BAR + 20 * 8;
constexpr uint32_t A_END = A_SS + 4 * 512;
constexpr int SMEM_BYTES = A_END - SB;
constexpr uint32_t A_STG = A_XR;
constexpr uint32_t A_WB = A_SEL;
constexpr uint32_t A_WA = A_XR + 49 * 1024;
constexpr uint32_t A_XO = A_QH + QP;
constexpr uint32_t A_W2A = A_BIN + 3072, A_W2B = A_BIN + 26624;
constexpr uint32_t A_OUT = A_W2A + 8192;
static_assert(A_W2A >= A_BIN + BIN1 && A_W2A + 8192 <= A_BIN + BIN1 + 7 * CB * 4 && A_W2B >= A_BIN + BIN1 + 17 * CB * 4 && A_W2B + 8192 <= A_BIN + DUMP && A_OUT + 8192 <= A_W2B, "alias");
static_assert(A_STG + (NCTA + 1) * SPITCH + 16 <= A_WA && A_WA + 2 * 10240 <= A_SEL && CB * 4 + 1024 <= BIN1 && BIN1 + 3 * CB * 4 <= 0x2000 && DUMP % 16 == 0 && 24 * CB / 128 < 128, "alias");
static_assert(A_W2A % 1024 == 0 && A_W2B % 1024 == 0 && A_QH % 1024 == 0 && QP % 1024 == 0 && A_WA % 1024 == 0 && A_SEL % 1024 == 0, "align");
static_assert(A_CNT % 16 == 0 && A_ZEND % 16 == 0 && A_B2 % 16 == 0 && A_B1 % 16 == 0 && A_BAR % 8 == 0 && A_BC % 16 == 0 && A_DEG % 8 == 0 && A_MISC % 16 == 0 && A_SS % 16 == 0, "align");
static_assert(SMEM_BYTES <= 199680 && A_ZEND - A_CNT <= 2048, "smem");

struct Scratch {
    uint32_t flag[NCTA * 32];
    uint32_t cnt, pad[31];
    uint4 x16[N_NODES * 8];
    uint4 ent[NCTA * NCTA * GPITCH];
};
__device__ __align__(128) Scratch g_scratch;

__device__ __forceinline__ void wg_fence() { asm volatile("wgmma.fence.sync.aligned;" ::: "memory"); }
__device__ __forceinline__ void wg_commit() { asm volatile("wgmma.commit_group.sync.aligned;" ::: "memory"); }
__device__ __forceinline__ void wg_wait0() { asm volatile("wgmma.wait_group.sync.aligned 0;" ::: "memory"); }
__device__ __forceinline__ void wg_wait1() { asm volatile("wgmma.wait_group.sync.aligned 1;" ::: "memory"); }
template <int M> __device__ __forceinline__ void fence_regs(uint32_t (&d)[M]) {
#pragma unroll
    for (int i = 0; i < M; i++) asm volatile("" : "+r"(d[i])::"memory");
}
template <int M> __device__ __forceinline__ void fence_regs(float (&d)[M]) {
#pragma unroll
    for (int i = 0; i < M; i++) asm volatile("" : "+f"(d[i])::"memory");
}
constexpr uint32_t HI128 = 0x40000040;
constexpr uint32_t HI32 = 0xC0000010;
template <int SC, uint32_t HI>
__device__ __forceinline__ void mma64h(uint32_t (&d)[16], const uint32_t (&a)[4], uint32_t lo) {
    asm volatile("{\n.reg .pred p;\n.reg .b64 dsc;\nsetp.ne.b32 p, %21, 0;\nmov.b64 dsc, {%20, %22};\n"
        "wgmma.mma_async.sync.aligned.m64n64k16.f16.f16.f16 {%0, %1, %2, %3, %4, %5, %6, %7, %8, %9, %10, %11, %12, %13, %14, %15}, {%16, %17, %18, %19}, dsc, p, 1, 1, 0;\n}\n"
        : "+r"(d[0]), "+r"(d[1]), "+r"(d[2]), "+r"(d[3]), "+r"(d[4]), "+r"(d[5]), "+r"(d[6]), "+r"(d[7]), "+r"(d[8]), "+r"(d[9]), "+r"(d[10]), "+r"(d[11]), "+r"(d[12]), "+r"(d[13]), "+r"(d[14]), "+r"(d[15])
        : "r"(a[0]), "r"(a[1]), "r"(a[2]), "r"(a[3]), "r"(lo), "n"(SC), "n"(HI));
}
template <uint32_t HI>
__device__ __forceinline__ void mma64h0(uint32_t (&d)[16], const uint32_t (&a)[4], uint32_t lo) {
    asm volatile("{\n.reg .pred p;\n.reg .b64 dsc;\nsetp.ne.b32 p, 0, 0;\nmov.b64 dsc, {%20, %21};\n"
        "wgmma.mma_async.sync.aligned.m64n64k16.f16.f16.f16 {%0, %1, %2, %3, %4, %5, %6, %7, %8, %9, %10, %11, %12, %13, %14, %15}, {%16, %17, %18, %19}, dsc, p, 1, 1, 0;\n}\n"
        : "=r"(d[0]), "=r"(d[1]), "=r"(d[2]), "=r"(d[3]), "=r"(d[4]), "=r"(d[5]), "=r"(d[6]), "=r"(d[7]), "=r"(d[8]), "=r"(d[9]), "=r"(d[10]), "=r"(d[11]), "=r"(d[12]), "=r"(d[13]), "=r"(d[14]), "=r"(d[15])
        : "r"(a[0]), "r"(a[1]), "r"(a[2]), "r"(a[3]), "r"(lo), "n"(HI));
}
template <uint32_t HI>
__device__ __forceinline__ void mma16t(uint32_t (&d)[4], uint32_t a0, uint32_t a1, uint32_t a2, uint32_t a3, uint32_t lo) {
    asm volatile("{\n.reg .pred p;\n.reg .b64 dsc;\nsetp.eq.b32 p, 0, 0;\nmov.b64 dsc, {%8, %9};\n"
        "wgmma.mma_async.sync.aligned.m64n16k16.f16.f16.f16 {%0, %1, %2, %3}, {%4, %5, %6, %7}, dsc, p, 1, 1, 1;\n}\n"
        : "+r"(d[0]), "+r"(d[1]), "+r"(d[2]), "+r"(d[3]) : "r"(a0), "r"(a1), "r"(a2), "r"(a3), "r"(lo), "n"(HI));
}
template <int SC, uint32_t HI>
__device__ __forceinline__ void mma96h(uint32_t (&d)[24], const uint32_t (&a)[4], uint32_t lo) {
    asm volatile("{\n.reg .pred p;\n.reg .b64 dsc;\nsetp.ne.b32 p, %29, 0;\nmov.b64 dsc, {%28, %30};\n"
        "wgmma.mma_async.sync.aligned.m64n96k16.f16.f16.f16 {%0, %1, %2, %3, %4, %5, %6, %7, %8, %9, %10, %11, %12, %13, %14, %15, %16, %17, %18, %19, %20, %21, %22, %23}, {%24, %25, %26, %27}, dsc, p, 1, 1, 0;\n}\n"
        : "+r"(d[0]), "+r"(d[1]), "+r"(d[2]), "+r"(d[3]), "+r"(d[4]), "+r"(d[5]), "+r"(d[6]), "+r"(d[7]), "+r"(d[8]), "+r"(d[9]), "+r"(d[10]), "+r"(d[11]), "+r"(d[12]), "+r"(d[13]), "+r"(d[14]), "+r"(d[15]), "+r"(d[16]), "+r"(d[17]), "+r"(d[18]), "+r"(d[19]), "+r"(d[20]), "+r"(d[21]), "+r"(d[22]), "+r"(d[23])
        : "r"(a[0]), "r"(a[1]), "r"(a[2]), "r"(a[3]), "r"(lo), "n"(SC), "n"(HI));
}
template <int SC>
__device__ __forceinline__ void mma64f(float (&d)[32], uint32_t la, uint32_t lb) {
    asm volatile("{\n.reg .pred p;\n.reg .b64 da, db;\nsetp.ne.b32 p, %34, 0;\nmov.b64 da, {%32, %35};\nmov.b64 db, {%33, %35};\n"
        "wgmma.mma_async.sync.aligned.m64n64k16.f32.f16.f16 {%0, %1, %2, %3, %4, %5, %6, %7, %8, %9, %10, %11, %12, %13, %14, %15, %16, %17, %18, %19, %20, %21, %22, %23, %24, %25, %26, %27, %28, %29, %30, %31}, da, db, p, 1, 1, 1, 0;\n}\n"
        : "+f"(d[0]), "+f"(d[1]), "+f"(d[2]), "+f"(d[3]), "+f"(d[4]), "+f"(d[5]), "+f"(d[6]), "+f"(d[7]), "+f"(d[8]), "+f"(d[9]), "+f"(d[10]), "+f"(d[11]), "+f"(d[12]), "+f"(d[13]), "+f"(d[14]), "+f"(d[15]), "+f"(d[16]), "+f"(d[17]), "+f"(d[18]), "+f"(d[19]), "+f"(d[20]), "+f"(d[21]), "+f"(d[22]), "+f"(d[23]), "+f"(d[24]), "+f"(d[25]), "+f"(d[26]), "+f"(d[27]), "+f"(d[28]), "+f"(d[29]), "+f"(d[30]), "+f"(d[31])
        : "r"(la), "r"(lb), "n"(SC), "n"(HI128));
}
template <int SC>
__device__ __forceinline__ void mma8f(float (&d)[4], uint32_t la, uint32_t lb) {
    asm volatile("{\n.reg .pred p;\n.reg .b64 da, db;\nsetp.ne.b32 p, %6, 0;\nmov.b64 da, {%4, %7};\nmov.b64 db, {%5, %7};\n"
        "wgmma.mma_async.sync.aligned.m64n8k16.f32.f16.f16 {%0, %1, %2, %3}, da, db, p, 1, 1, 1, 0;\n}\n"
        : "+f"(d[0]), "+f"(d[1]), "+f"(d[2]), "+f"(d[3]) : "r"(la), "r"(lb), "n"(SC), "n"(HI128));
}
__device__ __forceinline__ uint32_t hadd2(uint32_t a, uint32_t b) { uint32_t r; asm("add.rn.f16x2 %0, %1, %2;" : "=r"(r) : "r"(a), "r"(b)); return r; }
__device__ __forceinline__ uint32_t hfma2(uint32_t a, uint32_t b, uint32_t c) { uint32_t r; asm("fma.rn.f16x2 %0, %1, %2, %3;" : "=r"(r) : "r"(a), "r"(b), "r"(c)); return r; }
__device__ __forceinline__ uint32_t bfma2(uint32_t a, uint32_t b, uint32_t c) { uint32_t r; asm("fma.rn.bf16x2 %0, %1, %2, %3;" : "=r"(r) : "r"(a), "r"(b), "r"(c)); return r; }
template <uint32_t C> __device__ __forceinline__ uint32_t hfma2c(uint32_t a, uint32_t b) { uint32_t r; asm("fma.rn.f16x2 %0, %1, %2, %3;" : "=r"(r) : "r"(a), "r"(b), "r"(C * 0x10001u)); return r; }
__device__ __forceinline__ uint32_t silu_fma0(uint32_t u) {
    uint32_t au, t, p;
    asm("abs.f16x2 %0, %1;" : "=r"(au) : "r"(u));
    asm("fma.rn.sat.f16x2 %0, %1, %2, %3;" : "=r"(t) : "r"(au), "r"(0x15c515c5u), "r"(0x3bf23bf2u));
    const uint32_t f = hfma2(au, 0x41c541c5u, hfma2c<0x67f2>(t, 0xe800e800u));
    p = hfma2c<0xb58d>(hfma2c<0x2fc2>(f, 0xa6e2a6e2u), f);
    asm("fma.rn.sat.f16x2 %0, %0, %1, %2;" : "+r"(p) : "r"(f), "r"(0x38003800u));
    return hfma2c<0xb400>(p, t * (uint32_t)-1024 + (0x40004000u + 0x3bf23bf2u * 1024u));
}
__device__ __forceinline__ uint32_t silu_fma1(uint32_t u, uint32_t y) {
    uint32_t au;
    asm("abs.f16x2 %0, %1;" : "=r"(au) : "r"(u));
    uint32_t r = hfma2c<0x38be>(y, 0xb304b304u);
    r = hfma2c<0xbabc>(r, y);
    r = hfma2c<0x3c1e>(r, y);
    r = hfma2c<0xbd1e>(r, y);
    r = hfma2c<0x38cd>(r, y);
    return hfma2(au, r, u);
}
__device__ __forceinline__ uint32_t htanh2(uint32_t a) { uint32_t r; asm("tanh.approx.f16x2 %0, %1;" : "=r"(r) : "r"(a)); return r; }
__device__ __forceinline__ uint32_t pack_h2(float lo, float hi) { uint32_t r; asm("cvt.rn.f16x2.f32 %0, %1, %2;" : "=r"(r) : "f"(hi), "f"(lo)); return r; }
__device__ __forceinline__ uint32_t pack_b2(float lo, float hi) { uint32_t r; asm("cvt.rn.bf16x2.f32 %0, %1, %2;" : "=r"(r) : "f"(hi), "f"(lo)); return r; }
__device__ __forceinline__ uint32_t bf2h(uint32_t v) { return pack_h2(__uint_as_float(v << 16), __uint_as_float(v & 0xffff0000u)); }
__device__ __forceinline__ uint32_t bf2h_half(uint32_t v) { return pack_h2(0.5f * __uint_as_float(v << 16), 0.5f * __uint_as_float(v & 0xffff0000u)); }
__device__ __forceinline__ uint4 bf2h4(uint4 v) { return make_uint4(bf2h(v.x), bf2h(v.y), bf2h(v.z), bf2h(v.w)); }

__device__ __forceinline__ void cp16(uint32_t s, const void* g) { asm volatile("cp.async.cg.shared.global [%0], [%1], 16;" ::"r"(s), "l"(g) : "memory"); }
__device__ __forceinline__ void cp_commit() { asm volatile("cp.async.commit_group;" ::: "memory"); }
template <int N> __device__ __forceinline__ void cp_wait() { asm volatile("cp.async.wait_group %0;" ::"n"(N) : "memory"); }
__device__ __forceinline__ void bulk_g2s(uint32_t s, const void* g, uint32_t bytes, uint32_t bar) {
    asm volatile("cp.async.bulk.shared::cluster.global.mbarrier::complete_tx::bytes [%0], [%1], %2, [%3];" ::"r"(s), "l"(g), "r"(bytes), "r"(bar) : "memory");
}
__device__ __forceinline__ void tma_g2s(uint32_t s, const CUtensorMap* m, int c0, int c1, uint32_t bar) {
    asm volatile("cp.async.bulk.tensor.2d.shared::cluster.global.mbarrier::complete_tx::bytes [%0], [%1, {%2, %3}], [%4];" ::"r"(s), "l"(m), "r"(c0), "r"(c1), "r"(bar) : "memory");
}
__device__ __forceinline__ void l2_prefetch(const void* g, uint32_t bytes) { asm volatile("cp.async.bulk.prefetch.L2.global [%0], %1;" ::"l"(g), "r"(bytes) : "memory"); }
__device__ __forceinline__ void proxy_fence() { asm volatile("fence.proxy.async.shared::cta;" ::: "memory"); }
__device__ __forceinline__ bool mbar_try(uint32_t bar, uint32_t parity) {
    uint32_t ok;
    asm volatile("{\n.reg .pred p;\nmbarrier.try_wait.parity.shared::cta.b64 p, [%1], %2;\nselp.u32 %0, 1, 0, p;\n}" : "=r"(ok) : "r"(bar), "r"(parity) : "memory");
    return ok;
}
__device__ __forceinline__ bool mbar_test(uint32_t bar, uint32_t parity) {
    uint32_t ok;
    asm volatile("{\n.reg .pred p;\nmbarrier.test_wait.parity.shared::cta.b64 p, [%1], %2;\nselp.u32 %0, 1, 0, p;\n}" : "=r"(ok) : "r"(bar), "r"(parity) : "memory");
    return ok;
}
__device__ __forceinline__ void mbar_wait(uint32_t bar, uint32_t parity) {
    if (__builtin_expect(!mbar_try(bar, parity), 0))
        for (int it = 0; it < MBSPIN; it++) if (mbar_try(bar, parity)) break;
}
__device__ __forceinline__ void mbar_arrive(uint32_t bar) { asm volatile("mbarrier.arrive.shared::cta.b64 _, [%0];" ::"r"(bar) : "memory"); }
__device__ __forceinline__ uint32_t lds32(uint32_t a) { uint32_t r; asm volatile("ld.shared.u32 %0, [%1];" : "=r"(r) : "r"(a) : "memory"); return r; }
__device__ __forceinline__ uint32_t lds32_rlx(uint32_t a) { uint32_t r; asm volatile("ld.relaxed.cta.shared.u32 %0, [%1];" : "=r"(r) : "r"(a) : "memory"); return r; }
__device__ __forceinline__ uint32_t lds16(uint32_t a) { uint32_t r; asm volatile("ld.shared.u16 %0, [%1];" : "=r"(r) : "r"(a) : "memory"); return r; }
__device__ __forceinline__ uint2 lds64(uint32_t a) { uint2 r; asm volatile("ld.shared.v2.u32 {%0,%1}, [%2];" : "=r"(r.x), "=r"(r.y) : "r"(a) : "memory"); return r; }
__device__ __forceinline__ uint4 lds128(uint32_t a) { uint4 r; asm volatile("ld.shared.v4.u32 {%0,%1,%2,%3}, [%4];" : "=r"(r.x), "=r"(r.y), "=r"(r.z), "=r"(r.w) : "r"(a) : "memory"); return r; }
__device__ __forceinline__ void sts128(uint32_t a, uint4 v) { asm volatile("st.shared.v4.u32 [%0], {%1,%2,%3,%4};" ::"r"(a), "r"(v.x), "r"(v.y), "r"(v.z), "r"(v.w) : "memory"); }
__device__ __forceinline__ void sts64(uint32_t a, uint32_t x, uint32_t y) { asm volatile("st.shared.v2.u32 [%0], {%1,%2};" ::"r"(a), "r"(x), "r"(y) : "memory"); }
__device__ __forceinline__ void sts32(uint32_t a, uint32_t v) { asm volatile("st.shared.u32 [%0], %1;" ::"r"(a), "r"(v) : "memory"); }
__device__ __forceinline__ void sts16(uint32_t a, uint32_t v) { asm volatile("st.shared.u16 [%0], %1;" ::"r"(a), "r"(v) : "memory"); }
__device__ __forceinline__ void sts8(uint32_t a, uint32_t v) { asm volatile("st.shared.u8 [%0], %1;" ::"r"(a), "r"(v) : "memory"); }
__device__ __forceinline__ void sts32_z(uint32_t a, uint32_t v, uint32_t z) {
    asm volatile("{\n.reg .pred p;\nsetp.eq.u32 p, %2, 0;\n@p st.relaxed.cta.shared.u32 [%0], %1;\n}" ::"r"(a), "r"(v), "r"(z) : "memory");
}
__device__ __forceinline__ void sts32_lt(uint32_t a, uint32_t v, uint32_t x, uint32_t y) {
    asm volatile("{\n.reg .pred p;\nsetp.lt.u32 p, %2, %3;\n@p st.shared.u32 [%0], %1;\n}" ::"r"(a), "r"(v), "r"(x), "r"(y) : "memory");
}
__device__ __forceinline__ uint32_t atoms_inc(uint32_t a) { uint32_t r; asm volatile("atom.shared.add.u32 %0, [%1], 1;" : "=r"(r) : "r"(a) : "memory"); return r; }
__device__ __forceinline__ uint32_t bin_slot(uint32_t e) {
    uint32_t r;
    asm volatile("atom.shared.add.u32 %0, [%1], 4;" : "=r"(r) : "r"(A_BC + ((e >> 1) & 0x7c)) : "memory");
    return r;
}
__device__ __forceinline__ uint32_t bin_base(int b, int nb) { return b == 0 ? 0u : BIN1 + (b == nb - 1 ? 0 : b == 1 ? 1 : b == nb - 2 ? 2 : b + 1) * CB * 4; }
__device__ __forceinline__ void deg_inc(uint32_t v) { asm volatile("red.shared.add.u32 [%0], 1;" ::"r"(A_DEG + (v >> 22)) : "memory"); }
__device__ __forceinline__ uint32_t ldg_rlx32(const void* p) { uint32_t r; asm volatile("ld.relaxed.gpu.global.u32 %0, [%1];" : "=r"(r) : "l"(p) : "memory"); return r; }
#define LDI "ld.relaxed.gpu.global.v2.u32"
__device__ __forceinline__ int2 ldg64(const void* p) { int2 r; asm volatile(LDI " {%0,%1}, [%2];" : "=r"(r.x), "=r"(r.y) : "l"(p) : "memory"); return r; }
__device__ __forceinline__ void ldg64_if(int2& r, const void* p, bool on) {
    asm volatile("{\n.reg .pred p;\nsetp.ne.u32 p, %3, 0;\n@p " LDI " {%0,%1}, [%2];\n}" : "+r"(r.x), "+r"(r.y) : "l"(p), "r"((uint32_t)on) : "memory");
}
__device__ __forceinline__ uint4 ldg_rlx128_if(const void* p, bool on) {
    uint4 r;
    asm volatile("{\n.reg .pred p;\n.reg .b64 a, b;\nsetp.ne.u32 p, %5, 0;\n@p ld.relaxed.gpu.global.v2.b64 {a, b}, [%4];\nmov.b64 {%0,%1}, a;\nmov.b64 {%2,%3}, b;\n}"
                 : "=r"(r.x), "=r"(r.y), "=r"(r.z), "=r"(r.w) : "l"(p), "r"((uint32_t)on) : "memory");
    return r;
}
__device__ __forceinline__ void ldg_rlx128_upd(uint64_t& a, uint64_t& b, const void* p, bool on) {
    asm volatile("{\n.reg .pred p;\nsetp.ne.u32 p, %3, 0;\n@p ld.relaxed.gpu.global.v2.b64 {%0, %1}, [%2];\n}" : "+l"(a), "+l"(b) : "l"(p), "r"((uint32_t)on) : "memory");
}
__device__ __forceinline__ uint2 ldg_rlx64_if(const void* p, bool on) {
    uint64_t a = 0;
    asm volatile("{\n.reg .pred p;\nsetp.ne.u32 p, %2, 0;\n@p ld.relaxed.gpu.global.b64 %0, [%1];\n}" : "+l"(a) : "l"(p), "r"((uint32_t)on) : "memory");
    return make_uint2((uint32_t)a, (uint32_t)(a >> 32));
}
__device__ __forceinline__ void stg_rlx32(void* p, uint32_t v) { asm volatile("st.relaxed.gpu.global.u32 [%0], %1;" ::"l"(p), "r"(v) : "memory"); }
__device__ __forceinline__ void stg_rlx128(void* p, uint4 v) {
    asm volatile("{\n.reg .b64 a, b;\nmov.b64 a, {%1,%2};\nmov.b64 b, {%3,%4};\nst.relaxed.gpu.global.v2.b64 [%0], {a, b};\n}" ::"l"(p), "r"(v.x), "r"(v.y), "r"(v.z), "r"(v.w) : "memory");
}
__device__ __forceinline__ void stg_rlx128_if(void* p, uint4 v, bool on) {
    asm volatile("{\n.reg .pred p;\n.reg .b64 a, b;\nsetp.ne.u32 p, %5, 0;\nmov.b64 a, {%1,%2};\nmov.b64 b, {%3,%4};\n@p st.relaxed.gpu.global.v2.b64 [%0], {a, b};\n}" ::"l"(p), "r"(v.x), "r"(v.y), "r"(v.z), "r"(v.w), "r"((uint32_t)on) : "memory");
}
__device__ __forceinline__ void ldsm4t(uint32_t (&r)[4], uint32_t a) {
    asm volatile("ldmatrix.sync.aligned.m8n8.x4.trans.shared.b16 {%0,%1,%2,%3}, [%4];" : "=r"(r[0]), "=r"(r[1]), "=r"(r[2]), "=r"(r[3]) : "r"(a) : "memory");
}
__device__ __forceinline__ void ldsm2t(uint32_t& r0, uint32_t& r1, uint32_t a) {
    asm volatile("ldmatrix.sync.aligned.m8n8.x2.trans.shared.b16 {%0,%1}, [%2];" : "=r"(r0), "=r"(r1) : "r"(a) : "memory");
}
__device__ __forceinline__ void stsm2t(uint32_t a, uint32_t r0, uint32_t r1) {
    asm volatile("stmatrix.sync.aligned.m8n8.x2.trans.shared.b16 [%0], {%1,%2};" ::"r"(a), "r"(r0), "r"(r1) : "memory");
}
__device__ __forceinline__ void stsm4t(uint32_t a, uint32_t r0, uint32_t r1, uint32_t r2, uint32_t r3) {
    asm volatile("stmatrix.sync.aligned.m8n8.x4.trans.shared.b16 [%0], {%1,%2,%3,%4};" ::"r"(a), "r"(r0), "r"(r1), "r"(r2), "r"(r3) : "memory");
}
template <int ID, int N> __device__ __forceinline__ void bar_sync() { asm volatile("bar.sync %0, %1;" ::"n"(ID), "n"(N) : "memory"); }
template <int ID, int N> __device__ __forceinline__ void bar_arrive() { asm volatile("bar.arrive %0, %1;" ::"n"(ID), "n"(N) : "memory"); }
__device__ __forceinline__ uint32_t scan_up(uint32_t v) {
#pragma unroll
    for (int o = 1; o < 32; o <<= 1)
        asm volatile("{\n.reg .pred p;\n.reg .u32 t;\nshfl.sync.up.b32 t|p, %0, %1, 0, -1;\n@p add.u32 %0, %0, t;\n}" : "+r"(v) : "r"(o));
    return v;
}
__device__ __forceinline__ float bf2f(const __nv_bfloat16* p) { return __bfloat162float(*p); }

__device__ __forceinline__ int chunk_start(int c) { return c * CHUNK + min(c, 40) * 2; }
static_assert(NCTA * CHUNK + 80 == N_EDGES && CHUNK / 2 + 1 <= 6 * NP && CHUNK / 2 >= 5 * NP, "chunks");

struct Sched { uint32_t len, start, total; int L, L1, B0; bool fail; };
__device__ __forceinline__ Sched schedule(int lane, int nb) {
    Sched r;
    const uint32_t n = (lds32(A_BC + lane * 4) - bin_base(lane, nb)) >> 2, f = lds32(A_MISC);
    r.len = lane < nb ? max(n, (uint32_t)MINB) : 0u;
    const uint32_t end = scan_up(r.len);
    r.start = end - r.len;
    r.total = __shfl_sync(0xffffffffu, end, 31);
    r.L = (r.total + 127) >> 7;
    r.L1 = ((r.total + 63) >> 6) - r.L;
    r.B0 = __popc(__ballot_sync(0xffffffffu, end <= 64u * r.L));
    r.fail = __any_sync(0xffffffffu, r.len > CB || f);
    return r;
}
static_assert(64 * ((14 * MINB + 127) / 128) >= 2 * CB && 14 * MINB / 2 - 64 > 2 * CB && 14 * MINB / 2 - 64 - CB >= 7 * 64, "block B0 is never among the first two of a stream");

__device__ __noinline__ void slow_path(uint8_t* sp, const __nv_bfloat16* x, const __nv_bfloat16* ea, const int* src, const int* dst,
                                       const __nv_bfloat16* w1, const __nv_bfloat16* b1, const __nv_bfloat16* w2,
                                       const __nv_bfloat16* b2, __nv_bfloat16* out) {
    const int tid = threadIdx.x, lane = tid & 31, warp = tid >> 5, cta = blockIdx.x;
    const int nrows = min(NPC, N_NODES - cta * NPC);
    float* hs = (float*)sp;
    __nv_bfloat16* w1s = (__nv_bfloat16*)(sp + 192 * 128 * 4);
    int* dg = (int*)(sp + 192 * 128 * 4 + 144 * 128 * 2);
    __syncthreads();
    for (int i = tid; i < 192 * 128; i += NT) hs[i] = 0.f;
    for (int i = tid; i < 144 * 128; i += NT) w1s[i] = w1[i];
    for (int i = tid; i < 192; i += NT) dg[i] = 0;
    __syncthreads();
    float bb[4];
    for (int j = 0; j < 4; j++) bb[j] = bf2f(b1 + lane * 4 + j);
    for (int i0 = warp * 32; i0 < N_EDGES; i0 += NT) {
        const int mine = dst[i0 + lane] - cta * NPC;
        uint32_t hit = __ballot_sync(0xffffffffu, (unsigned)mine < (unsigned)nrows);
        while (hit) {
            const int b = __ffs(hit) - 1;
            hit &= hit - 1;
            const int eid = i0 + b, dl = __shfl_sync(0xffffffffu, mine, b), s = src[eid];
            float v[5];
            v[0] = bf2f(x + s * 64 + lane); v[1] = bf2f(x + s * 64 + 32 + lane);
            v[2] = bf2f(x + (cta * NPC + dl) * 64 + lane); v[3] = bf2f(x + (cta * NPC + dl) * 64 + 32 + lane);
            v[4] = lane < 16 ? bf2f(ea + (size_t)eid * 16 + lane) : 0.f;
            float z[4] = {bb[0], bb[1], bb[2], bb[3]};
#pragma unroll
            for (int c = 0; c < 5; c++) {
                for (int kk = 0; kk < (c == 4 ? 16 : 32); kk++) {
                    float a = __shfl_sync(0xffffffffu, v[c], kk);
                    const __nv_bfloat16* wr = w1s + (c * 32 + kk) * 128 + lane * 4;
#pragma unroll
                    for (int j = 0; j < 4; j++) z[j] = fmaf(a, __bfloat162float(wr[j]), z[j]);
                }
            }
#pragma unroll
            for (int j = 0; j < 4; j++) atomicAdd(&hs[dl * 128 + lane * 4 + j], z[j] / (1.f + expf(-z[j])));
            if (lane == 0) atomicAdd(&dg[dl], 1);
        }
    }
    __syncthreads();
    for (int i = tid; i < nrows * 64; i += NT) {
        int n = i >> 6, d = i & 63;
        float a = 0.f;
        if (dg[n] > 0) {
            a = (float)dg[n] * bf2f(b2 + d);
            for (int h = 0; h < 128; h++) a = fmaf(hs[n * 128 + h], bf2f(w2 + h * 64 + d), a);
        }
        out[(size_t)(cta * NPC + n) * 64 + d] = __float2bfloat16(a);
    }
}

__global__ void __launch_bounds__(NT, 1)
mpnn_kernel(const __nv_bfloat16* __restrict__ x, const __nv_bfloat16* __restrict__ ea, const int* __restrict__ src,
            const int* __restrict__ dst, const __nv_bfloat16* __restrict__ w1, const __nv_bfloat16* __restrict__ b1,
            const __nv_bfloat16* __restrict__ w2, const __nv_bfloat16* __restrict__ b2, __nv_bfloat16* __restrict__ out,
            Scratch* __restrict__ gs, const __grid_constant__ CUtensorMap w1map) {
    extern __shared__ uint8_t smem_raw[];
    const int tid = threadIdx.x, lane = tid & 31;
    __builtin_assume(tid < NT);
    const int warp = __shfl_sync(0xffffffffu, tid >> 5, 0);
    const int cta = blockIdx.x;
    const int nrows = min(NPC, N_NODES - cta * NPC), nb = (nrows + 7) >> 3;
    const int e0 = chunk_start(cta);
    const int nv2 = CHUNK / 2 + (cta < 40);
    if ((uint32_t)__cvta_generic_to_shared(smem_raw) != SB || !gs) { slow_path(smem_raw, x, ea, src, dst, w1, b1, w2, b2, out); return; }
    constexpr uint32_t bar_w = A_BAR + R * 16, bar_x = bar_w + 8, bar_r = bar_x + 8;
    const int wg = warp >> 2, wq = warp & 3, hh = wg & 1, strm = wg >> 1;
    const uint32_t qch = wq * 2 + ((lane >> 3) & 1);
    const uint32_t wofs = (((lane >> 4) & 1) * 8 + (lane & 7)) * 128 + ((qch ^ (lane & 7)) << 4);
    int bad = 0;

    int2 d2[6];
    const int pt = tid - NP;
    if (wg == 4) {
        uint32_t cnt0;
        if (pt == 64) cnt0 = ldg_rlx32(&gs->cnt);
        if (pt == 96) {
#pragma unroll
            for (int i = 0; i < 2 * R + 3; i++) asm volatile("mbarrier.init.shared::cta.b64 [%0], %1;" ::"r"(A_BAR + i * 8), "r"(i < R ? 2 : i < 2 * R ? 8 : i < 2 * R + 2 ? 1 : NT / 32) : "memory");
            proxy_fence();
            asm volatile("mbarrier.arrive.expect_tx.shared::cta.b64 _, [%0], %1;" ::"r"(bar_w), "r"(144 * 256 + 256 + 128) : "memory");
            asm volatile("mbarrier.arrive.expect_tx.shared::cta.b64 _, [%0], %1;" ::"r"(bar_x), "r"(nrows * 128) : "memory");
        }
        __syncwarp();
        stg_rlx128_if((uint4*)gs->flag + cta * 8 + (lane & 1), make_uint4(0, 0, 0, 0), pt < 2);
        if (pt < (int)(A_ZEND - A_CNT) / 16) sts128(A_CNT + pt * 16, make_uint4(0, 0, 0, 0));
        if (pt == 64) {
            const uint32_t tag = cnt0 / NCTA + 1;
            sts64(A_TAG, tag << 21, tag >> 11 << 21);
        }
    } else {
        const int2* dp = (const int2*)(dst + e0) + tid;
        d2[5] = make_int2(NCTA * NPC, NCTA * NPC);
#pragma unroll
        for (int r = 0; r < 5; r++) d2[r] = ldg64(dp + r * NP);
        ldg64_if(d2[5], dp + 5 * NP, tid < nv2 - 5 * NP);
        stg_rlx128_if(gs->ent + ((tid >> 1) * NCTA + cta) * GPITCH + (lane & 1), make_uint4(0, 0, 0, 0), tid < 2 * NCTA);
    }
    __syncthreads();
    const uint2 tag = lds64(A_TAG);
    if (wg == 4) {
        const uint32_t tagw = tag.x | tag.y >> 11;
        if (warp == 19) {
            if (lane == 0) {
                bulk_g2s(A_XO, x + cta * NPC * 64, nrows * 128, bar_x);
                asm volatile("red.relaxed.gpu.global.inc.u32 [%0], %1;" ::"l"(&gs->cnt), "r"(NCTA * TAGMOD - 1) : "memory");
            }
            __syncwarp();
            if (lane < 18) {
                int i = lane + cta % 18;
                i = i >= 18 ? i - 18 : i;
                const int h = i & 1, rb = i >> 1;
                tma_g2s(rb >= 4 && rb < 8 ? A_WB + h * 8192 + (rb - 4) * 2048 : A_WA + h * 10240 + min(rb, 4) * 2048, &w1map, h * 64, rb * 16, bar_w);
            } else if (lane < 20) bulk_g2s(lane == 18 ? A_B1 : A_B2, lane == 18 ? b1 : b2, lane == 18 ? 256 : 128, bar_w);
            else if (lane == 20) l2_prefetch(w2, 128 * 64 * 2);
            __syncwarp();
        }
        if (warp == 16) sts32(A_BC + lane * 4, lane < 24 ? bin_base(lane, nb) : DUMP);
#pragma unroll 1
        for (uint32_t a = A_BIN + pt * 16; a < A_BIN + DUMP; a += 2048) sts128(a, make_uint4(EMPTY, EMPTY, EMPTY, EMPTY));
        bar_arrive<1, NT>();
        mbar_wait(bar_x, 0);
        const uint32_t xo = A_XO + (pt >> 3) * 128 + (((pt ^ (pt >> 3)) & 7) << 4);
        {
            uint4 xr[12];
#pragma unroll
            for (int r = 0; r < 12; r++) xr[r] = lds128(A_XO + (r * 128 + pt) * 16);
            __syncwarp();
#pragma unroll
            for (int r = 0; r < 12; r++) {
                const bool in = r * 128 + pt < nrows * 8;
                const uint4 v = in ? bf2h4(xr[r]) : make_uint4(0, 0, 0, 0);
                sts128(xo + r * 2048, v);
                if (in) gs->x16[cta * NPC * 8 + r * 128 + pt] = v;
            }
        }
        bar_arrive<2, 160>();
        proxy_fence();
        mbar_wait(bar_w, 0);
        bar_sync<4, 128>();
#pragma unroll 1
        for (int h = 0; h < 2; h++) {
            uint32_t wb[4][4], acc[2][24];
#pragma unroll
            for (int i = 0; i < 4; i++) ldsm4t(wb[i], A_WB + h * 8192 + wofs + i * 2048);
            const uint32_t bl0 = lds16(A_B1 + (h * 64 + wq * 16 + (lane >> 2)) * 2), bl1 = lds16(A_B1 + (h * 64 + wq * 16 + 8 + (lane >> 2)) * 2);
#pragma unroll
            for (int i = 0; i < 4; i++)
#pragma unroll
                for (int j = 0; j < 4; j++) wb[i][j] = bf2h_half(wb[i][j]);
            const uint32_t bq0 = bf2h_half(bl0 * 0x10001u), bq1 = bf2h_half(bl1 * 0x10001u);
#pragma unroll
            for (int i = 0; i < 4; i++) fence_regs(wb[i]);
            wg_fence();
#pragma unroll
            for (int n = 0; n < 2; n++) {
                const uint32_t lo = ((A_XO >> 4) | 0x10000) + n * 768;
                mma96h<0, HI128>(acc[n], wb[0], lo);
                mma96h<1, HI128>(acc[n], wb[1], lo + 2);
                mma96h<1, HI128>(acc[n], wb[2], lo + 4);
                mma96h<1, HI128>(acc[n], wb[3], lo + 6);
            }
            wg_commit();
            wg_wait0();
            fence_regs(acc[0]); fence_regs(acc[1]);
            if (h) {
                bar_sync<4, 128>();
            }
#pragma unroll
            for (int n = 0; n < 2; n++)
#pragma unroll
                for (int j = 0; j < 6; j++)
                    stsm4t(A_QH + h * QP + n * 12288 + wofs + j * 2048, hadd2(acc[n][4 * j], bq0), hadd2(acc[n][4 * j + 1], bq1), hadd2(acc[n][4 * j + 2], bq0), hadd2(acc[n][4 * j + 3], bq1));
        }
        if (pt == 64) l2_prefetch(src + cta * 6064, min(6064, N_EDGES - cta * 6064) * 4);
        const int par = wq >> 1, hf = wq & 1, gq = lane >> 3, cp = (lane >> 1) & 3;
        const uint32_t sel = A_SEL + hf * 2048 + (par * 32 + lane) * 32 + ((lane >> 2) & 1) * 16;
#pragma unroll
        for (int r = 0; r < 8; r++) sts128(A_SEL + hf * 2048 + par * 1024 + (r >> 1) * 4096 + (r & 1) * 512 + lane * 16, make_uint4(0, 0, 0, 0));
        const uint32_t bar_full = A_BAR + hf * 8, bar_empty = bar_full + R * 8;
        uint32_t xd[8];
#pragma unroll
        for (int c = 0; c < 8; c++) xd[c] = A_XR + hf * 8192 + (par * 32 + gq * 8) * 128 + (((lane & 7) ^ c) << 4);
        fence_regs(xd);
        uint32_t ed0 = A_ER + hf * 2048 + (par * 32 + gq * 8 + cp) * 32 + (lane & 1) * 16, ed1 = (ed0 ^ 16) + 128;
        const uint32_t sw = A_SS + wq * 128 + lane * 4, sr = A_SS + wq * 128 + gq * 32;
        const char* xg = (const char*)gs->x16 + (lane & 7) * 16;
        const char* eg = (const char*)ea + (lane & 1) * 16;
        const char* sp = (const char*)src;
        int bi = hf ? nb - 1 : 0;
        uint32_t ta = A_BIN + hf * BIN1 + (par * 32 + lane) * 4;
        asm volatile("" : "+l"(xg), "+l"(eg), "+l"(sp), "+r"(ed0), "+r"(ed1), "+r"(ta));
        uint32_t prev[4] = {sel, sel, sel, sel}, own[4], col[4];
        auto issue_e = [&](int st, uint32_t e) {
            const uint32_t e0 = __shfl_sync(0xffffffffu, e, gq * 8 + cp), e1 = __shfl_sync(0xffffffffu, e, gq * 8 + cp + 4);
            cp16(ed0 + st * 4096, eg + (size_t)(e0 & 0xfffff) * 32);
            cp16(ed1 + st * 4096, eg + (size_t)(e1 & 0xfffff) * 32);
            col[st] = e;
        };
        auto issue_x = [&](int st, const uint4& a0, const uint4& a1) {
            const uint32_t a[8] = {a0.x, a0.y, a0.z, a0.w, a1.x, a1.y, a1.z, a1.w};
#pragma unroll
            for (int i = 0; i < 8; i++) cp16(xd[i] + st * 16384 + i * 128, xg + (size_t)a[i] * 128);
        };
        auto fetch_src = [&](int slot, uint32_t e) {
            asm volatile("cp.async.ca.shared.global [%0], [%1], 4;" ::"r"(sw + slot * 512), "l"(sp + (size_t)(e & 0xfffff) * 4) : "memory");
        };
        auto prep = [&](int u) {
            const uint4 v0 = lds128(ed0 + u * 4096), v1 = lds128(ed1 + u * 4096);
            sts16(prev[u] + u * 4096, 0);
            prev[u] = sel ^ ((col[u] >> 23) & 0x1e);
            sts16(prev[u] + u * 4096, col[u] < (192u << 24) ? 0x3c00 : 0);
            deg_inc(col[u]);
            sts128(ed0 + u * 4096, bf2h4(v0));
            sts128(ed1 + u * 4096, bf2h4(v1));
        };
        auto done = [&](int u) {
            proxy_fence();
            __syncwarp();
            if (lane == 0) mbar_arrive(bar_full + u * 16);
        };
        auto finish = [&](int u) { prep(u); done(u); };
        __syncwarp();
        if (lane == 0) mbar_arrive(bar_r);
        auto flags = [&]() {
            const uint32_t* fp = gs->flag + (wq * 33 + lane) * 32;
#pragma unroll 1
            for (int it = 0;; it++) {
                const uint32_t f0 = ldg_rlx32(fp), f1 = ldg_rlx32(gs->flag + (wq * 33 + 32) * 32);
                if (__all_sync(0xffffffffu, f0 == tagw && f1 == tagw)) break;
                if (it >= SPIN) { bad = 1; break; }
                __nanosleep(100);
            }
            asm volatile("fence.acquire.gpu;" ::: "memory");
        };
        bar_sync<12, NT>();
#pragma unroll
        for (int t = 0; t < 2; t++) {
#pragma unroll 1
            for (int it = 0; it < MBSPIN; it++) {
                const bool all = mbar_test(bar_r, 0);
                col[t] = lds32_rlx(ta + t * 256);
                if (__all_sync(0xffffffffu, all || col[t] != EMPTY)) break;
                __nanosleep(40);
            }
            const uint32_t ea = ta + t * 256 + (gq * 8 + cp - lane) * 4;
            const uint32_t a0 = lds32_rlx(ea), a1 = lds32_rlx(ea + 16);
            fetch_src(t, col[t]);
            cp_commit();
            cp16(ed0 + t * 4096, eg + (size_t)(a0 & 0xfffff) * 32);
            cp16(ed1 + t * 4096, eg + (size_t)(a1 & 0xfffff) * 32);
            cp_commit();
        }
        ta += 256;
        cp_wait<2>();
        prep(0);
        flags();
        bar_sync<4, 128>();
        issue_x(0, lds128(sr), lds128(sr + 16));
        cp_commit();
        mbar_wait(bar_r, 0);
        uint32_t bs = A_BIN + bin_base(lane, nb), be = max(A_BIN + lds32(A_BC + lane * 4), bs + MINB * 4);
        const int dir = hf ? -1 : 1;
        uint32_t nx = __shfl_sync(0xffffffffu, be, bi);
        auto next_entry = [&]() {
            ta += 256;
            while (__builtin_expect(__any_sync(0xffffffffu, ta >= nx), 0)) {
                const bool c = ta >= nx;
                if (c) bi += dir;
                const uint32_t s2 = __shfl_sync(0xffffffffu, bs, bi), e2 = __shfl_sync(0xffffffffu, be, bi);
                if (c) { ta += s2 - nx; nx = e2; }
            }
            return lds32(ta);
        };
        own[2] = next_entry();
        own[3] = next_entry();
        fetch_src(2, own[2]);
        fetch_src(3, own[3]);
        cp_commit();
        cp_wait<3>();
        __syncwarp();
        issue_x(1, lds128(sr + 512), lds128(sr + 512 + 16));
        cp_commit();
        cp_wait<2>();
        done(0);
        issue_e(2, own[2]);
        issue_e(3, own[3]);
        cp_commit();
        prep(1);
        cp_wait<2>();
        __syncwarp();
        issue_x(2, lds128(sr + 1024), lds128(sr + 1024 + 16));
        cp_commit();
        cp_wait<2>();
        done(1);
        bar_sync<5, NT>();
        own[0] = next_entry();
        own[1] = next_entry();
        fetch_src(0, own[0]);
        fetch_src(1, own[1]);
        cp_commit();
        own[2] = next_entry();
        issue_x(3, lds128(sr + 1536), lds128(sr + 1536 + 16));
        fetch_src(2, own[2]);
        cp_commit();
        cp_wait<3>();
        prep(2);
        cp_wait<2>();
        done(2);
        asm volatile("bar.sync %0, 96;" ::"r"(6 + hf * 5) : "memory");
        const uint4 sc = lds128(A_MISC);
        if (!sc.x) {
            const int L = (sc.z >> hf * 8) & 255;
            if (lane == sc.y) { const uint32_t cut = bs + (sc.z >> 16); if (hf) bs = cut; else be = cut; }
            if (lane == sc.y + dir) { bs = A_BIN + CB * 4; be = ~0u; }
            cp_wait<1>();
            __syncwarp();
            const bool early = sc.y - 11 < 2;
            const int jw = early ? 10 + L - (int)((sc.z >> 8) & 255) : -4;
            auto w2_fetch = [&]() {
                bar_sync<4, 128>();
#pragma unroll
                for (int i = 0; i < 8; i++) cp16(A_W2A - A_XO + xo + (i >> 2) * (A_W2B - A_W2A) + (i & 3) * 2048, (const uint4*)w2 + i * 128 + pt);
            };
            auto w2_convert = [&]() {
#pragma unroll
                for (int i = 0; i < 8; i++) {
                    const uint32_t a = A_W2A - A_XO + xo + (i >> 2) * (A_W2B - A_W2A) + (i & 3) * 2048;
                    sts128(a, bf2h4(lds128(a)));
                }
            };
            uint32_t ph = 1;
            for (int j = L;; j -= 4) {
#pragma unroll
                for (int u = 2; u < 6; u++) {
                    if (j == u) goto done;
                    if (u == 2 && __builtin_expect(j < jw + 4, 0)) {
                        if (j >= jw) w2_fetch();
                        else if (j >= jw - 4) w2_convert();
                    }
                    if (u == 2) ph ^= 1;
                    const int st = (u + 2) & 3;
                    if (j > u + 2) {
                        const uint32_t es = next_entry();
                        const uint4 a0 = lds128(sr + st * 512), a1 = lds128(sr + st * 512 + 16);
                        fetch_src((st + 3) & 3, es);
                        mbar_wait(bar_empty + st * 16, ph);
                        issue_e(st, own[st]);
                        issue_x(st, a0, a1);
                        own[(st + 3) & 3] = es;
                    } else mbar_wait(bar_empty + st * 16, ph);
                    cp_commit();
                    if (u < 4 && j == L) {
                        if (u == 2) { cp_wait<1>(); finish(3); }
                    } else {
                        cp_wait<2>();
                        finish(u & 3);
                    }
                }
            }
        done:
            if (lane == 0) mbar_arrive(bar_full + (L & 3) * 16);
            if (!early) {
                w2_fetch();
                cp_commit();
                cp_wait<0>();
                w2_convert();
            }
            proxy_fence();
            const float bo0 = __uint_as_float(lds16(A_B2 + (wq * 16 + (lane >> 2)) * 2) << 16);
            const float bo1 = __uint_as_float(lds16(A_B2 + (wq * 16 + 8 + (lane >> 2)) * 2) << 16);
            const int late = early ? 2 : 0;
            bar_sync<4, 128>();
#pragma unroll 1
            for (int p = 0; p < 3; p++) {
                const int rb = p == 2 ? 64 : p * 128, j0 = sc.y - (rb >> 3);
                float d[32], d1[4], dg[16];
#pragma unroll
                for (int j = 0; j < 8; j++) {
                    const uint2 v = lds64(A_DEG + (rb + j * 8 + (lane & 3) * 2) * 4);
                    dg[2 * j] = __uint_as_float(v.x + 0x4b000000) - 8388608.f; dg[2 * j + 1] = __uint_as_float(v.y + 0x4b000000) - 8388608.f;
                }
                fence_regs(dg);
                if (p == late) bar_sync<3, NT>();
                constexpr uint32_t la = (A_W2A >> 4) | 0x10000, lq = (A_QH >> 4) | 0x10000, lb = (A_W2B - A_W2A) / 16;
                wg_fence();
                mma64f<0>(d, la, lq + rb * 8);
#pragma unroll
                for (int i = 1; i < 8; i++) mma64f<1>(d, la + (i >> 2) * lb + (i & 3) * 128, lq + rb * 8 + (i >> 2) * (QP / 16) + (i & 3) * 2);
                wg_commit();
                if ((unsigned)j0 < 8) {
                    wg_fence();
                    mma8f<0>(d1, la, lq + 24 * 64);
#pragma unroll
                    for (int i = 1; i < 8; i++) mma8f<1>(d1, la + (i >> 2) * lb + (i & 3) * 128, lq + 24 * 64 + (i >> 2) * (QP / 16) + (i & 3) * 2);
                    wg_commit();
                }
                wg_wait0();
                fence_regs(d); fence_regs(d1);
                uint32_t r[16], nf = 0;
#pragma unroll
                for (int j = 0; j < 8; j++) {
                    if (j == j0) { d[4 * j] += d1[0]; d[4 * j + 1] += d1[1]; d[4 * j + 2] += d1[2]; d[4 * j + 3] += d1[3]; }
                    r[2 * j] = pack_b2(fmaf(dg[2 * j], bo0, d[4 * j]), fmaf(dg[2 * j + 1], bo0, d[4 * j + 1]));
                    r[2 * j + 1] = pack_b2(fmaf(dg[2 * j], bo1, d[4 * j + 2]), fmaf(dg[2 * j + 1], bo1, d[4 * j + 3]));
                    nf = bfma2(r[2 * j], 0, bfma2(r[2 * j + 1], 0, nf));
                }
                bad |= nf & 0x7fff7fff;
                const uint32_t ob = p ? A_QH - 16384 + p * 16384 : A_OUT, oa = ob + ((lane >> 4) * 8 + (lane & 7)) * 128 + ((qch ^ (lane & 7)) << 4);
#pragma unroll
                for (int j = 0; j < 4; j++) stsm4t(oa + j * 2048, r[4 * j], r[4 * j + 1], r[4 * j + 2], r[4 * j + 3]);
                bar_sync<4, 128>();
#pragma unroll
                for (int j = 0; j < 4; j++) {
                    const int row = j * 16 + wq * 4 + (lane >> 3);
                    const uint4 v = lds128(ob + row * 128 + (((lane ^ row) & 7) << 4));
                    if (rb + row < nrows) ((uint4*)out)[(cta * NPC + rb + row) * 8 + (lane & 7)] = v;
                }
            }
        } else bad = 1;
        cp_wait<0>();
    } else {
        const uint32_t jn = 192 + (lane & 3) * 8 + (lane & 16) * 2, ja = tag.x + jn, jb = tag.y + jn;
        const int nr = warp < NCTA / 2 - 64 ? 5 : 4, half = lane >> 4;
        {
            uint32_t c[12], rk[12];
#pragma unroll
            for (int i = 0; i < 12; i++) {
                c[i] = __umulhi(i & 1 ? d2[i >> 1].y : d2[i >> 1].x, 44151u << 9);
                rk[i] = atoms_inc(A_CNT + c[i] * 4);
            }
            const uint32_t tb = tag.y + (tid << 9), td = tag.x - tag.y;
#pragma unroll
            for (int i = 0; i < 12; i++)
                sts32(A_STG + 4 + c[i] * SPITCH + min(rk[i], (uint32_t)CAP) * 4,
                      (i & 1 ? d2[i >> 1].y : d2[i >> 1].x) + tb + (((i >> 1) * NP * 2 + (i & 1)) << 8) - c[i] * NPC + (rk[i] & 1) * td);
        }
        bar_sync<1, NT>();
        {
            const uint32_t row = warp * 2 + half, p0 = (lane & 15) * 4;
            uint4* gp = gs->ent + (row * NCTA + cta) * GPITCH + (lane & 15);
            const uint32_t sp = A_STG + row * SPITCH + (lane & 15) * 16;
            uint32_t n[5];
            uint4 v[5];
#pragma unroll
            for (int k = 0; k < 5; k++) {
                n[k] = lds32(A_CNT + min(row + k * 32, NCTA + 1) * 4);
                v[k] = lds128(sp + k * 32 * SPITCH);
            }
            uint32_t big = 0;
#pragma unroll
            for (int k = 0; k < 5; k++) {
                if (p0 - 1 >= n[k]) v[k].x = p0 ? ja : ja + (n[k] << 8);
                if (p0 + 1 > n[k]) v[k].y = jb;
                if (p0 + 2 > n[k]) v[k].z = ja;
                if (p0 + 3 > n[k]) v[k].w = jb;
                stg_rlx128_if(gp + k * 32 * NCTA * GPITCH, v[k], (p0 & ~7u) <= n[k] && (k < 4 || nr == 5));
                if (n[k] >= 64 && (k < 4 || nr == 5)) big |= 1u << k;
            }
            while (__builtin_expect(big != 0, 0)) {
                const int k = __ffs(big) - 1;
                big &= big - 1;
                const uint32_t m = lds32(A_CNT + (row + k * 32) * 4), p = p0 + 64;
                if (p0 < 32 && (p & ~7u) <= m) {
                    uint4 u = lds128(sp + k * 32 * SPITCH + 256);
                    if (p > m) u.x = ja;
                    if (p + 1 > m) u.y = jb;
                    if (p + 2 > m) u.z = ja;
                    if (p + 3 > m) u.w = jb;
                    stg_rlx128(gp + k * 32 * NCTA * GPITCH + 16, u);
                }
            }
            __syncwarp();
        }
        uint32_t w[5][4];
        mbar_wait(bar_w, 0);
#pragma unroll
        for (int i = 0; i < 5; i++) ldsm4t(w[i], A_WA + hh * 10240 + wofs + i * 2048);
#pragma unroll
        for (int i = 0; i < 5; i++) {
#pragma unroll
            for (int j = 0; j < 4; j++) w[i][j] = bf2h_half(w[i][j]);
            fence_regs(w[i]);
        }
        bar_arrive<12, NT>();
        if (warp == 15) {
            bar_sync<2, 160>();
            asm volatile("fence.release.gpu;" ::: "memory");
            if (lane == 0) stg_rlx32(gs->flag + cta * 32, tag.x | tag.y >> 11);
            __syncwarp();
        }
        const uint4* rp = gs->ent + (cta * NCTA + warp * 2) * GPITCH;
        const uint4* hp = rp + (min(lane >> 1, 4) * 32 + (lane & 1)) * GPITCH;
        rp += half * GPITCH + (lane & 15);
        uint64_t en[10];
        uint32_t rk[20];
#pragma unroll
        for (int i = 0; i < 10; i++) en[i] = ja | (uint64_t)jb << 32;
        const uint32_t row0 = warp * 2 + half, cx = row0 * CHUNK - (tag.x >> 8), cy = row0 * CHUNK - (tag.y >> 8);
        const uint32_t ce[2] = {row0 * 2, min(row0 + 32, 40u) * 2};
        int nl = -1;
        bool fail = false;
        uint32_t pend = (1u << 2 * nr) - 1, todo = (1u << nr) - 1, got = 0;
        for (int it = 0;; it++) {
            const uint2 h = ldg_rlx64_if(hp, (pend >> lane) & 1);
            uint32_t next = 0;
#pragma unroll
            for (int k = 0; k < 5; k++) {
                if (got & (1u << k)) {
                    const uint32_t a = en[2 * k], b = en[2 * k] >> 32, c = en[2 * k + 1], d = en[2 * k + 1] >> 32;
                    if (__builtin_expect(__any_sync(0xffffffffu, ((a ^ tag.x) | (b ^ tag.y) | (c ^ tag.x) | (d ^ tag.y)) >= (1u << 21)), 0)) next |= 1u << k;
                    else {
                        rk[4 * k] = bin_slot(a);
                        rk[4 * k + 1] = bin_slot(b);
                        rk[4 * k + 2] = bin_slot(c);
                        rk[4 * k + 3] = bin_slot(d);
                    }
                }
            }
#pragma unroll
            for (int k = 0; k < 5; k++) {
                if (got & ~next & (1u << k)) {
                    const uint32_t cs = k * 32 * CHUNK + (k < 2 ? ce[k & 1] : 80);
                    uint32_t v[4];
#pragma unroll
                    for (int j = 0; j < 4; j++) {
                        const uint32_t e = en[2 * k + (j >> 1)] >> (j & 1) * 32;
                        v[j] = __funnelshift_r(e, e, 8) + (cs + (j & 1 ? cy : cx));
                        sts32_z(A_BIN + rk[4 * k + j], v[j], rk[4 * k + j] & ~0x1fffu);
                    }
                    en[2 * k] = v[0] | (uint64_t)v[1] << 32;
                    en[2 * k + 1] = v[2] | (uint64_t)v[3] << 32;
                }
            }
            uint32_t hd;
            asm volatile("{\n.reg .u32 t;\nshr.u32 t, %5, 5;\nlop3.b32 t, %1, %2, t, 0xbe;\nlop3.b32 %0, %3, %4, t, 0xbe;\n}" : "=r"(hd) : "r"(h.x), "r"(tag.x), "r"(h.y), "r"(tag.y), "r"(next));
            const bool ok = hd < (1u << 21) && ((pend >> lane) & 1);
            if (ok) nl = (h.x >> 8) & 0x1fff;
            if (ok && nl > CAP) { fail = true; nl = -1; }
            pend &= ~__ballot_sync(0xffffffffu, ok);
            uint32_t seen = 0;
#pragma unroll
            for (int k = 0; k < 5; k++) if (!(pend & (3u << 2 * k))) seen |= 1u << k;
            seen &= todo;
            todo &= ~seen;
            got = next | seen;
            if (!(got | todo)) break;
            if (it >= SPIN) { fail = true; nl = -1; break; }
            if (got) {
                const int q = min(nl >> 3, 7);
                const uint32_t b0 = __ballot_sync(0xffffffffu, q & 1), b1 = __ballot_sync(0xffffffffu, q & 2), b2 = __ballot_sync(0xffffffffu, q & 4);
                uint32_t g = lane & 2 ? b0 : ~0u;
                g = lane & 4 ? b1 & g : b1 | g;
                g = lane & 8 ? b2 & g : b2 | g;
                g >>= half;
#pragma unroll
                for (int k = 0; k < 5; k++) ldg_rlx128_upd(en[2 * k], en[2 * k + 1], rp + k * 32 * GPITCH, (got >> k) & (g >> 2 * k) & 1);
            }
            uint32_t big = __ballot_sync(0xffffffffu, ok && nl >= 64);
            while (__builtin_expect(big != 0, 0)) {
                uint32_t m = big;
#pragma unroll
                for (int g = 0; g < 4; g++) { if (g < lane >> 3) m &= m - 1; big &= big - 1; }
                const int k = __ffs(m) - 1, n = __shfl_sync(0xffffffffu, nl, k), row = (k >> 1) * 32 + warp * 2 + (k & 1), p = 64 + 4 * (lane & 7);
                if (m && p <= n) {
                    uint4 ex;
                    bool bad = true;
                    for (int it = 0; it < SPIN; it++) {
                        ex = ldg_rlx128_if(gs->ent + (cta * NCTA + row) * GPITCH + p / 4, true);
                        bad = ((ex.x ^ tag.x) | (ex.y ^ tag.y) | (ex.z ^ tag.x) | (ex.w ^ tag.y)) >= (1u << 21);
                        if (!bad) break;
                    }
                    if (bad) fail = true;
                    else {
#pragma unroll
                        for (int j = 0; j < 4; j++) {
                            const uint32_t a = j == 0 ? ex.x : j == 1 ? ex.y : j == 2 ? ex.z : ex.w;
                            if (p + j <= n) sts32_z(A_BIN + min(bin_slot(a), DUMP), (a << 24) + ((a >> 8) & 0x1fff) + chunk_start(row), 0);
                        }
                    }
                }
                __syncwarp();
            }
        }
        if (fail) sts32(A_MISC, 1);
        __syncwarp();
        if (lane == 0) mbar_arrive(bar_r);
        mbar_wait(bar_r, 0);
        if (!fail) {
#pragma unroll
            for (int i = 0; i < 20; i++)
                if (i < 16 || nr == 5) sts32_lt(A_BIN + rk[i], en[i >> 1] >> (i & 1) * 32, rk[i] - 0x2000, DUMP - 0x2000);
        }
        bar_arrive<5, NT>();
        const uint32_t qb = A_QH + hh * QP + (lane & 7) * 128 + ((qch ^ (lane & 7)) << 4);
        uint32_t acc[2][16], h[16], q[4], s[4], t0, y3;
        ldsm4t(q, qb + (lane < 16 ? strm * ((nb - 1) & ~1) : strm * (nb - 2) | 1) * 1024);
#pragma unroll
        for (int i = 0; i < 4; i++) s[i] = 0;
#pragma unroll
        for (int i = 0; i < 5; i++) fence_regs(w[i]);
        fence_regs(q); fence_regs(s);
        uint32_t eva = A_EV + strm * 128;
        const int fd = strm ? 2048 : -2048;
        const uint32_t lox = ((A_XR >> 4) | 0x10000) + strm * 512, loe = ((A_ER >> 4) | 0x10000) + strm * 128, los = ((A_SEL >> 4) | 0x10000) + strm * 128;
        const uint32_t bar_full = A_BAR + strm * 8, bar_empty = bar_full + R * 8;
        auto gemm = [&](int st, uint32_t ph, uint32_t (&d)[16]) {
            mbar_wait(bar_full + st * 16, ph);
            wg_fence();
            mma64h0<HI128>(d, w[0], lox + st * 1024);
            mma64h<1, HI128>(d, w[1], lox + st * 1024 + 2);
            mma64h<1, HI128>(d, w[2], lox + st * 1024 + 4);
            mma64h<1, HI128>(d, w[3], lox + st * 1024 + 6);
            mma64h<1, HI32>(d, w[4], loe + st * 256);
            mma64h<1, HI32>(d, q, los + st * 256);
            wg_commit();
        };
        uint32_t ph = 0, clk = 0;
        if ((warp & 7) == 5) {
            const Sched sd = schedule(lane, nb);
            if (!sd.fail) {
                if (strm ? lane >= sd.B0 && lane < nb - 2 : lane >= 2 && lane <= sd.B0) sts8(A_EV + strm * 128 - 1 + ((strm ? sd.total - sd.start - sd.len : sd.start) >> 6), lane + (strm && lane == sd.B0 ? 96 : 32));
                if (lane == 0) sts8(A_EV + strm * 128 + (strm ? sd.L1 : sd.L), 255);
                if (lane == sd.B0) { sts32(A_MISC + 4, sd.B0); sts32(A_MISC + 8, sd.L | sd.L1 << 8 | (64 * sd.L - sd.start) * 4 << 16); }
            } else sts32(A_MISC, 1);
            asm volatile("bar.arrive %0, 96;" ::"r"(6 + strm * 5) : "memory");
        }
        asm volatile("bar.sync %0, 256;" ::"r"(13 + strm) : "memory");
        const bool give_up = lds32(A_MISC);
        gemm(0, 0, acc[0]);
        wg_wait0();
        fence_regs(acc[0]);

        if (!give_up) {
        if (lane == 0) mbar_arrive(bar_empty);
        t0 = htanh2(acc[0][0]);
        y3 = silu_fma0(acc[0][3]);
        for (;;) {
            const uint32_t evw = lds32(eva);
#pragma unroll
            for (int st = 0; st < 4; st++) {
                const uint32_t ev = (evw >> 8 * st) & 255;
                if (__builtin_expect(ev != 0, 0)) {
                    if (ev == 255) goto finished;
                    const uint32_t qa = qb - 32 * 1024 + (ev & 63) * 1024, fa = qa + fd;
                    if (ev & 1) { stsm2t(fa, s[2], s[3]); ldsm2t(q[2], q[3], qa); s[2] = 0; s[3] = 0; }
                    else { stsm2t(fa, s[0], s[1]); ldsm2t(q[0], q[1], qa); s[0] = 0; s[1] = 0; }
                    __syncwarp();
                    if (ev & 64) bar_arrive<15, 512>();
                    fence_regs(s); fence_regs(q);
                }
                uint32_t (&u)[16] = acc[st & 1];
                uint32_t (&v)[16] = acc[(st + 1) & 1];
                if (st == 3) ph ^= 1;
                gemm((st + 1) & 3, ph, v);
#pragma unroll
                for (int i = 0; i < 16; i++) {
                    if (i == 3) { fence_regs(h); asm volatile("mov.u32 %0, %%clock;" : "=r"(clk)::"memory"); fence_regs(u); }
                    h[i] = i == 3 || i == 15 ? silu_fma1(u[i], i == 3 ? y3 : silu_fma0(u[i])) : hfma2(u[i], i ? htanh2(u[i]) : t0, u[i]);
                }
                wg_fence();
#pragma unroll
                for (int k = 0; k < 4; k++) mma16t<HI32>(s, h[4 * k], h[4 * k + 1], h[4 * k + 2], h[4 * k + 3], los + (st & 3) * 256 + k * 32);
                wg_commit();
                wg_wait1();
                fence_regs(v);
                if (lane == 0) mbar_arrive(bar_empty + ((st + 1) & 3) * 16);
                t0 = htanh2(v[0]);
                y3 = silu_fma0(v[3]);
                asm volatile("" : "+r"(t0), "+r"(y3)::"memory");
                wg_wait0();
                fence_regs(s);
            }
            eva += 4;
        }
    finished:
        const uint2 ms = lds64(A_MISC);
        {
            const bool odd = ms.y & 1;
            const uint32_t a = qb + ms.y * 1024;
            stsm2t(a + fd / 2, odd ? s[0] : s[2], odd ? s[1] : s[3]);
            if (!strm) bar_sync<15, 512>();
            stsm2t(strm ? qb + 24 * 1024 : a, odd ? s[2] : s[0], odd ? s[3] : s[1]);
            bad = clk & ms.x;
        }
        proxy_fence();
        bar_arrive<3, NT>();
        } else bad = 1;
    }
    if (__syncthreads_or(bad)) slow_path(smem_raw, x, ea, src, dst, w1, b1, w2, b2, out);
}

}

extern "C" void kernel_launch(void* const* d_in, const int* in_sizes, int n_in, void* d_out, int out_size) {
    typedef CUresult (*EncodeFn)(CUtensorMap*, CUtensorMapDataType, cuuint32_t, void*, const cuuint64_t*, const cuuint64_t*, const cuuint32_t*,
                                 const cuuint32_t*, CUtensorMapInterleave, CUtensorMapSwizzle, CUtensorMapL2promotion, CUtensorMapFloatOOBfill);
    static bool init = false;
    static EncodeFn encode = nullptr;
    static void* scratch = nullptr;
    if (!init) {
        cudaFuncSetAttribute(mpnn_kernel, cudaFuncAttributeMaxDynamicSharedMemorySize, SMEM_BYTES);
        void* fn = nullptr;
        cudaDriverEntryPointQueryResult st;
        if (cudaGetDriverEntryPoint("cuTensorMapEncodeTiled", &fn, cudaEnableDefault, &st) == cudaSuccess && st == cudaDriverEntryPointSuccess) encode = (EncodeFn)fn;
        if (cudaGetSymbolAddress(&scratch, g_scratch) != cudaSuccess) scratch = nullptr;
        init = true;
    }
    CUtensorMap map = {};
    const cuuint64_t dims[2] = {128, 144}, strides[1] = {256};
    const cuuint32_t box[2] = {64, 16}, estr[2] = {1, 1};
    const bool have_map = encode && encode(&map, CU_TENSOR_MAP_DATA_TYPE_BFLOAT16, 2, d_in[4], dims, strides, box, estr, CU_TENSOR_MAP_INTERLEAVE_NONE,
                                          CU_TENSOR_MAP_SWIZZLE_128B, CU_TENSOR_MAP_L2_PROMOTION_NONE, CU_TENSOR_MAP_FLOAT_OOB_FILL_NONE) == CUDA_SUCCESS;
    mpnn_kernel<<<NCTA, NT, SMEM_BYTES>>>((const __nv_bfloat16*)d_in[0], (const __nv_bfloat16*)d_in[1], (const int*)d_in[2], (const int*)d_in[3],
                                          (const __nv_bfloat16*)d_in[4], (const __nv_bfloat16*)d_in[5], (const __nv_bfloat16*)d_in[6],
                                          (const __nv_bfloat16*)d_in[7], (__nv_bfloat16*)d_out, have_map ? (Scratch*)scratch : nullptr, map);
}
```
